```python
import torch

def _softmax(x, axis=-1):
    return torch.softmax(x, dim=axis)
def _gelu(x):
    return torch.nn.functional.gelu(x, approximate="tanh")
def _silu(x):
    return torch.nn.functional.silu(x)
def _sigmoid(x):
    return torch.sigmoid(x)
def _layernorm(x, axis=-1, eps=1e-5):
    m = x.mean(dim=axis, keepdim=True)
    v = x.var(dim=axis, keepdim=True, unbiased=False)
    return (x - m) / torch.sqrt(v + eps)
def _scatter_add(tgt, idx, src, axis=0):
    return tgt.clone().index_add_(axis, idx, src)
def _segment_sum(src, seg, n):
    out = torch.zeros((n,) + src.shape[1:], dtype=src.dtype)
    return out.index_add_(0, seg, src)
def _pad(x, pw):
    flat = tuple(v for pair in reversed(pw) for v in pair)
    return torch.nn.functional.pad(x, flat)

kernel_name = 'concat_heads__gqa_block_cached__mha_block_cached__near_ridge'

def setup_inputs():

    _w = (lambda a: (lambda t: t.to(torch.bfloat16) if t.is_floating_point() else t)(torch.as_tensor(a)))
    def _A_setup():
        B, Sq, D = 8, 144, 512
        Hq, Hkv, Sk, Dh = 32, 32, 512, 128
        assert Hq % Hkv == 0, (Hq, Hkv)
        return {
            "x": _w((lambda *s: torch.randn(*s, dtype=torch.bfloat16) * 0.8)(B, Sq, D)),
            "k_cache": _w((lambda *s: torch.randn(*s, dtype=torch.bfloat16) * 0.8)(B, Hkv, Sk, Dh)),
            "v_cache": _w((lambda *s: torch.randn(*s, dtype=torch.bfloat16) * 0.05)(B, Hkv, Sk, Dh)),
            "wq": _w((lambda *s: torch.randn(*s, dtype=torch.bfloat16) * 0.8)(D, Hq * Dh) * (D ** -0.5)),
            "wo": _w((lambda *s: torch.randn(*s, dtype=torch.bfloat16) * 0.05)(Hq * Dh, D) * ((Hq * Dh) ** -0.5)),
        }
    _A_in = _A_setup()

    def _B_setup():
        B, Sq, D = 8, 144, 512
        H, Sk, Dh = 32, 512, 128
        return {
            "x": _w((lambda *s: torch.randn(*s, dtype=torch.bfloat16) * 0.8)(B, Sq, D)),
            "k_cache": _w((lambda *s: torch.randn(*s, dtype=torch.bfloat16) * 0.8)(B, H, Sk, Dh)),
            "v_cache": _w((lambda *s: torch.randn(*s, dtype=torch.bfloat16) * 0.05)(B, H, Sk, Dh)),
            "wq": _w((lambda *s: torch.randn(*s, dtype=torch.bfloat16) * 0.8)(D, H * Dh) * (D ** -0.5)),
            "wo": _w((lambda *s: torch.randn(*s, dtype=torch.bfloat16) * 0.05)(H * Dh, D) * ((H * Dh) ** -0.5)),
        }
    _B_in = _B_setup()

    return {
        "A_x": _A_in["x"],
        "A_k_cache": _A_in["k_cache"],
        "A_v_cache": _A_in["v_cache"],
        "A_wq": _A_in["wq"],
        "A_wo": _A_in["wo"],
        "B_x": _B_in["x"],
        "B_k_cache": _B_in["k_cache"],
        "B_v_cache": _B_in["v_cache"],
        "B_wq": _B_in["wq"],
        "B_wo": _B_in["wo"],
    }

def reference(A_x, A_k_cache, A_v_cache, A_wq, A_wo, B_x, B_k_cache, B_v_cache, B_wq, B_wo):
    def _A_ref(x, k_cache, v_cache, wq, wo):
        B, Sq, D = x.shape
        Hq, Dh = 32, 128
        Hkv = k_cache.shape[1]
        rep = Hq // Hkv
        q = (lambda x, *d: x.permute(*d))((x @ wq).reshape(B, Sq, Hq, Dh), 0, 2, 1, 3)
        k = (lambda x, n, axis: torch.repeat_interleave(x, n, dim=axis))(k_cache, rep, axis=1)
        v = (lambda x, n, axis: torch.repeat_interleave(x, n, dim=axis))(v_cache, rep, axis=1)
        scores = torch.einsum("bhqd,bhkd->bhqk", q, k) * (Dh ** -0.5)
        p = _softmax(scores, axis=-1)
        o = torch.einsum("bhqk,bhkd->bhqd", p, v)
        return (lambda x, *d: x.permute(*d))(o, 0, 2, 1, 3).reshape(B, Sq, Hq * Dh) @ wo

    def _B_ref(x, k_cache, v_cache, wq, wo):
        B, Sq, D = x.shape
        H, Dh = 32, 128
        q = (lambda x, *d: x.permute(*d))((x @ wq).reshape(B, Sq, H, Dh), 0, 2, 1, 3)
        scores = torch.einsum("bhqd,bhkd->bhqk", q, k_cache) * (Dh ** -0.5)
        p = _softmax(scores, axis=-1)
        o = torch.einsum("bhqk,bhkd->bhqd", p, v_cache)
        return (lambda x, *d: x.permute(*d))(o, 0, 2, 1, 3).reshape(B, Sq, H * Dh) @ wo

    a = _A_ref(A_x, A_k_cache, A_v_cache, A_wq, A_wo)
    b = _B_ref(B_x, B_k_cache, B_v_cache, B_wq, B_wo)
    return torch.concatenate([a, b], axis=-1)
```

```cpp
#include <cuda_runtime.h>
#include <cuda_bf16.h>
#include <cuda.h>
#include <stdint.h>

#define FAST_FLAGS
#define NO_GATE
#define REMAP

namespace {

constexpr int SQ = 144, DM = 512, NH = 32, SK = 512, DH = 128, NB = 8;
#define FINE_ITEM 0
constexpr int NCTA = 128;
constexpr int NTHREADS = 512;

#define CFG_PROMO CU_TENSOR_MAP_L2_PROMOTION_NONE
#define CFG_PROMO_KV CU_TENSOR_MAP_L2_PROMOTION_NONE
#define CFG_NP 2
#define CFG_NAUX 2
#define CFG_NKV 5
#define CFG_REG_PROD 24
#define CFG_REG_S 136
#define CFG_REG_O 176
constexpr int REG_PROD = CFG_REG_PROD, REG_S = CFG_REG_S, REG_O = CFG_REG_O;
static_assert(REG_PROD + REG_S + 2 * REG_O <= 512, "regs");
#define CFG_KVFLIGHT 2
constexpr int KVFLIGHT = CFG_KVFLIGHT;
#define CFG_KVSLOW 16
constexpr int KVSLOW = CFG_KVSLOW;
#define QLD_AT 7
constexpr int NP = CFG_NP, NAUX = CFG_NAUX, NKV = CFG_NKV;

constexpr uint32_t BT = SQ * 128;
constexpr uint32_t AT = 16384;
constexpr uint32_t AUX_SLOT = BT + AT;
constexpr uint32_t OFF_Q = 0;
constexpr uint32_t OFF_P = 2 * BT;
constexpr uint32_t OFF_AUX = OFF_P + NP * BT;
constexpr uint32_t OFF_KV = OFF_AUX + NAUX * AUX_SLOT;
constexpr uint32_t OFF_MISC = OFF_KV + NKV * AT;
constexpr uint32_t OFF_BAR = OFF_MISC;
constexpr uint32_t OFF_INVL = OFF_BAR + 512;
constexpr uint32_t OFF_LRED = OFF_INVL + 576;
constexpr uint32_t OFF_BAD = OFF_LRED + 2304;
constexpr uint32_t OFF_EPOCH = OFF_BAD + 16;
constexpr uint32_t OFF_PROF = OFF_BAD + 64;
constexpr uint32_t SMEM_BYTES = OFF_PROF;
static_assert(SMEM_BYTES <= 232448, "smem");

constexpr int B_K_FULL = 0, B_V_FULL = 8, B_KV_EMPTY = 16, B_AUXQ_FULL = 24, B_AUXO_FULL = 28, B_AUX_EMPTY = 32, B_P_FULL = 36, B_P_EMPTY = 38,
              B_Q_FULL = 40, B_L_FULL = 41, B_O_STAGED = 42, B_X_FULL = 43, B_PV_DONE = 44  , B_QA_FULL = 52, B_O_FREE = 53, B_QLD = 54, B_FREEQ = 56  ;
static_assert(NKV <= 8 && NAUX == 2 && NP == 2, "barrier table");

__host__ __device__ constexpr uint32_t aux_off(uint32_t s) { return s < 2 ? OFF_AUX + s * AUX_SLOT : (s == 2 ? OFF_Q : OFF_P); }

__host__ __device__ constexpr uint32_t wide_slot(uint32_t k) { return (0x02310210u >> (4 * k)) & 3u; }
__host__ __device__ constexpr bool wide_release(uint32_t k) { return k != 5 && k != 6; }

__host__ __device__ constexpr uint32_t q_slot(uint32_t k) { return (0x02102102u >> (4 * k)) & 3u; }

struct Params {
  CUtensorMap x[2], wq[2], k[2], v[2], wo[2];
};

struct RawPtrs { const __nv_bfloat16 *x[2], *wq[2], *k[2], *v[2]; __nv_bfloat16* out; };

#define CFG_OBUF 2
constexpr int OBUF = CFG_OBUF;
__device__ __align__(1024) unsigned char g_O[OBUF * 16 * 8 * 2 * BT];
__device__ __align__(16) unsigned g_flagO[16 * 32];
__device__ unsigned g_cons[16 * 2 * 4];
__device__ unsigned g_epoch;
__device__ unsigned g_done;

#define FINE(idx)
#define PROF(role, idx)
#define PROFT(role, idx)

__device__ __forceinline__ uint32_t smem_u32(const void* p) { return (uint32_t)__cvta_generic_to_shared(p); }
__device__ __forceinline__ void mbar_init(uint32_t bar, uint32_t cnt) { asm volatile("mbarrier.init.shared::cta.b64 [%0], %1;" :: "r"(bar), "r"(cnt)); }
__device__ __forceinline__ void mbar_expect_tx(uint32_t bar, uint32_t bytes) { asm volatile("mbarrier.arrive.expect_tx.shared::cta.b64 _, [%0], %1;" :: "r"(bar), "r"(bytes) : "memory"); }
__device__ __forceinline__ void mbar_arrive_n(uint32_t bar, uint32_t n) { asm volatile("mbarrier.arrive.shared::cta.b64 _, [%0], %1;" :: "r"(bar), "r"(n) : "memory"); }
__device__ __forceinline__ void mbar_arrive(uint32_t bar) { asm volatile("mbarrier.arrive.shared::cta.b64 _, [%0];" :: "r"(bar) : "memory"); }
__device__ __forceinline__ bool mbar_try(uint32_t bar, uint32_t parity) {
  uint32_t ok;
  asm volatile("{\n.reg .pred p;\nmbarrier.try_wait.parity.shared::cta.b64 p, [%1], %2;\nselp.u32 %0, 1, 0, p;\n}" : "=r"(ok) : "r"(bar), "r"(parity) : "memory");
  return ok;
}
#define WAIT_TIMEOUT(n, code) if (++(n) > (1u << 22)) __trap();
__device__ __forceinline__ void mbar_wait(uint32_t bar, uint32_t parity) {
  if (mbar_try(bar, parity)) return;
  uint32_t n = 0;
  while (!mbar_try(bar, parity)) { WAIT_TIMEOUT(n, ((bar & 0x1ff) >> 3) | (parity << 8)) }
}
__device__ __forceinline__ void fence_proxy_async() { asm volatile("fence.proxy.async.shared::cta;" ::: "memory"); }
__device__ __forceinline__ void fence_proxy_async_all() { asm volatile("fence.proxy.async;" ::: "memory"); }
__device__ __forceinline__ void wgmma_fence() { asm volatile("wgmma.fence.sync.aligned;" ::: "memory"); }
__device__ __forceinline__ void wgmma_commit() { asm volatile("wgmma.commit_group.sync.aligned;" ::: "memory"); }
template<int N> __device__ __forceinline__ void wgmma_wait() { asm volatile("wgmma.wait_group.sync.aligned %0;" :: "n"(N) : "memory"); }
template<int N> __device__ __forceinline__ void fence_regs(float (&d)[N]) {
  #pragma unroll
  for (int i = 0; i < N; i++) asm volatile("" : "+f"(d[i]) :: "memory");
}
__device__ __forceinline__ void named_bar(int id, int n) { asm volatile("bar.sync %0, %1;" :: "r"(id), "r"(n) : "memory"); }
__device__ __forceinline__ bool named_bar_or(int id, int n, bool v) {
  uint32_t r;
  asm volatile("{\n.reg .pred p, q;\nsetp.ne.u32 q, %3, 0;\nbar.red.or.pred p, %1, %2, q;\nselp.u32 %0, 1, 0, p;\n}" : "=r"(r) : "r"(id), "r"(n), "r"((uint32_t)v) : "memory");
  return r;
}
__device__ __forceinline__ void tma2d(uint32_t dst, const CUtensorMap* tm, int c0, int c1, uint32_t bar) {
  asm volatile("cp.async.bulk.tensor.2d.shared::cluster.global.mbarrier::complete_tx::bytes [%0], [%1, {%3, %4}], [%2];"
    :: "r"(dst), "l"(tm), "r"(bar), "r"(c0), "r"(c1) : "memory");
}
__device__ __forceinline__ void tma3d(uint32_t dst, const CUtensorMap* tm, int c0, int c1, int c2, uint32_t bar) {
  asm volatile("cp.async.bulk.tensor.3d.shared::cluster.global.mbarrier::complete_tx::bytes [%0], [%1, {%3, %4, %5}], [%2];"
    :: "r"(dst), "l"(tm), "r"(bar), "r"(c0), "r"(c1), "r"(c2) : "memory");
}
__device__ __forceinline__ void tma3d_hint(uint32_t dst, const CUtensorMap* tm, int c0, int c1, int c2, uint32_t bar, uint64_t pol) {
  asm volatile("cp.async.bulk.tensor.3d.shared::cluster.global.mbarrier::complete_tx::bytes.L2::cache_hint [%0], [%1, {%3, %4, %5}], [%2], %6;"
    :: "r"(dst), "l"(tm), "r"(bar), "r"(c0), "r"(c1), "r"(c2), "l"(pol) : "memory");
}
__device__ __forceinline__ void bulk_g2s(uint32_t dst, const void* src, uint32_t bytes, uint32_t bar) {
  asm volatile("cp.async.bulk.shared::cluster.global.mbarrier::complete_tx::bytes [%0], [%1], %2, [%3];" :: "r"(dst), "l"(src), "r"(bytes), "r"(bar) : "memory");
}
__device__ __forceinline__ void bulk_s2g(void* dst, uint32_t src, uint32_t bytes) {
  asm volatile("cp.async.bulk.global.shared::cta.bulk_group [%0], [%1], %2;" :: "l"(dst), "r"(src), "r"(bytes) : "memory");
}
__device__ __forceinline__ void tma2d_store(const CUtensorMap* tm, uint32_t src, int c0, int c1) {
  asm volatile("cp.async.bulk.tensor.2d.global.shared::cta.bulk_group [%0, {%2, %3}], [%1];" :: "l"(tm), "r"(src), "r"(c0), "r"(c1) : "memory");
}
__device__ __forceinline__ void bulk_commit() { asm volatile("cp.async.bulk.commit_group;" ::: "memory"); }
__device__ __forceinline__ void bulk_wait_read() { asm volatile("cp.async.bulk.wait_group.read 0;" ::: "memory"); }
__device__ __forceinline__ void bulk_wait_all() { asm volatile("cp.async.bulk.wait_group 0;" ::: "memory"); }
__device__ __forceinline__ unsigned ld_acquire(const unsigned* p) { unsigned v; asm volatile("ld.acquire.gpu.global.u32 %0, [%1];" : "=r"(v) : "l"(p) : "memory"); return v; }
__device__ __forceinline__ void st_release(unsigned* p, unsigned v) { asm volatile("st.release.gpu.global.u32 [%0], %1;" :: "l"(p), "r"(v) : "memory"); }
__device__ __forceinline__ void red_release_add(unsigned* p, unsigned v) { asm volatile("red.release.gpu.global.add.u32 [%0], %1;" :: "l"(p), "r"(v) : "memory"); }
__device__ __forceinline__ void wait_flag_eq(const unsigned* p, unsigned want) {
  uint32_t n = 0;
  while (ld_acquire(p) != want) { WAIT_TIMEOUT(n, 0x1000) }
}
__device__ __forceinline__ uint32_t poll_flags4(const unsigned* p, unsigned want) {
  uint32_t a, b, c, d;
  asm volatile("ld.volatile.global.v4.u32 {%0, %1, %2, %3}, [%4];" : "=r"(a), "=r"(b), "=r"(c), "=r"(d) : "l"(p) : "memory");
  return (a == want ? 1u : 0u) | (b == want ? 2u : 0u) | (c == want ? 4u : 0u) | (d == want ? 8u : 0u);
}
__device__ __forceinline__ void st_relaxed(unsigned* p, unsigned v) { asm volatile("st.relaxed.gpu.global.u32 [%0], %1;" :: "l"(p), "r"(v) : "memory"); }
#define CONS_FENCE()
__device__ __forceinline__ void fence_acq_gpu() { asm volatile("fence.acq_rel.gpu;" ::: "memory"); }
__device__ __forceinline__ uint32_t mapa(uint32_t addr, uint32_t cta) { uint32_t r; asm("mapa.shared::cluster.u32 %0, %1, %2;" : "=r"(r) : "r"(addr), "r"(cta)); return r; }
__device__ __forceinline__ void st_async_v4(uint32_t addr, float a, float b, float c, float d, uint32_t mbar) {
  asm volatile("st.async.weak.shared::cluster.mbarrier::complete_tx::bytes.v4.f32 [%0], {%1, %2, %3, %4}, [%5];" :: "r"(addr), "f"(a), "f"(b), "f"(c), "f"(d), "r"(mbar) : "memory");
}
__device__ __forceinline__ void mbar_wait_cluster(uint32_t bar, uint32_t parity) {
  uint32_t ok, n = 0;
  do {
    asm volatile("{\n.reg .pred p;\nmbarrier.try_wait.parity.acquire.cluster.shared::cta.b64 p, [%1], %2;\nselp.u32 %0, 1, 0, p;\n}" : "=r"(ok) : "r"(bar), "r"(parity) : "memory");
    if (!ok && ++n > (1u << 22)) __trap();
  } while (!ok);
}
__device__ __forceinline__ float ex2(float x) { float y; asm("ex2.approx.ftz.f32 %0, %1;" : "=f"(y) : "f"(x)); return y; }
__device__ __forceinline__ uint32_t pack_bf16(float lo, float hi) { uint32_t r; asm("cvt.rn.bf16x2.f32 %0, %1, %2;" : "=r"(r) : "f"(hi), "f"(lo)); return r; }
__device__ __forceinline__ void stsm_x2_t(uint32_t addr, uint32_t r0, uint32_t r1) {
  asm volatile("stmatrix.sync.aligned.m8n8.x2.trans.shared.b16 [%0], {%1, %2};" :: "r"(addr), "r"(r0), "r"(r1) : "memory");
}
__device__ __forceinline__ uint32_t bf16x2_chk(uint32_t u, uint32_t v, uint32_t c) { uint32_t r; asm("fma.rn.bf16x2 %0, %1, %2, %3;" : "=r"(r) : "r"(u), "r"(v), "r"(c)); return r; }
__device__ __forceinline__ void prefetch3d(const CUtensorMap* tm, int c0, int c1, int c2) {
  asm volatile("cp.async.bulk.prefetch.tensor.3d.L2.global.tile [%0, {%1, %2, %3}];" :: "l"(tm), "r"(c0), "r"(c1), "r"(c2) : "memory");
}
__device__ __forceinline__ void prefetch2d(const CUtensorMap* tm, int c0, int c1) {
  asm volatile("cp.async.bulk.prefetch.tensor.2d.L2.global.tile [%0, {%1, %2}];" :: "l"(tm), "r"(c0), "r"(c1) : "memory");
}
__device__ __forceinline__ void stsm_x4_t(uint32_t addr, uint32_t r0, uint32_t r1, uint32_t r2, uint32_t r3) {
  asm volatile("stmatrix.sync.aligned.m8n8.x4.trans.shared.b16 [%0], {%1, %2, %3, %4};" :: "r"(addr), "r"(r0), "r"(r1), "r"(r2), "r"(r3) : "memory");
}
__device__ __forceinline__ uint64_t make_desc(uint32_t addr) {
  return (uint64_t)((addr & 0x3FFFF) >> 4) | ((uint64_t)1 << 16) | ((uint64_t)(1024 >> 4) << 32) | ((uint64_t)1 << 62);
}
template<int TA> __device__ __forceinline__ void wgmma144(float (&d)[72], uint64_t da, uint64_t db, int scale_d) {
  asm volatile("{\n.reg .pred p;\nsetp.ne.b32 p, %74, 0;\n"
    "wgmma.mma_async.sync.aligned.m64n144k16.f32.bf16.bf16 "
    "{%0, %1, %2, %3, %4, %5, %6, %7, %8, %9, %10, %11, "
    "%12, %13, %14, %15, %16, %17, %18, %19, %20, %21, %22, %23, "
    "%24, %25, %26, %27, %28, %29, %30, %31, %32, %33, %34, %35, "
    "%36, %37, %38, %39, %40, %41, %42, %43, %44, %45, %46, %47, "
    "%48, %49, %50, %51, %52, %53, %54, %55, %56, %57, %58, %59, "
    "%60, %61, %62, %63, %64, %65, %66, %67, %68, %69, %70, %71}, "
    "%72, %73, p, 1, 1, %75, 0;\n}\n"
    : "+f"(d[0]), "+f"(d[1]), "+f"(d[2]), "+f"(d[3]), "+f"(d[4]), "+f"(d[5]), "+f"(d[6]), "+f"(d[7]),
      "+f"(d[8]), "+f"(d[9]), "+f"(d[10]), "+f"(d[11]), "+f"(d[12]), "+f"(d[13]), "+f"(d[14]), "+f"(d[15]),
      "+f"(d[16]), "+f"(d[17]), "+f"(d[18]), "+f"(d[19]), "+f"(d[20]), "+f"(d[21]), "+f"(d[22]), "+f"(d[23]),
      "+f"(d[24]), "+f"(d[25]), "+f"(d[26]), "+f"(d[27]), "+f"(d[28]), "+f"(d[29]), "+f"(d[30]), "+f"(d[31]),
      "+f"(d[32]), "+f"(d[33]), "+f"(d[34]), "+f"(d[35]), "+f"(d[36]), "+f"(d[37]), "+f"(d[38]), "+f"(d[39]),
      "+f"(d[40]), "+f"(d[41]), "+f"(d[42]), "+f"(d[43]), "+f"(d[44]), "+f"(d[45]), "+f"(d[46]), "+f"(d[47]),
      "+f"(d[48]), "+f"(d[49]), "+f"(d[50]), "+f"(d[51]), "+f"(d[52]), "+f"(d[53]), "+f"(d[54]), "+f"(d[55]),
      "+f"(d[56]), "+f"(d[57]), "+f"(d[58]), "+f"(d[59]), "+f"(d[60]), "+f"(d[61]), "+f"(d[62]), "+f"(d[63]),
      "+f"(d[64]), "+f"(d[65]), "+f"(d[66]), "+f"(d[67]), "+f"(d[68]), "+f"(d[69]), "+f"(d[70]), "+f"(d[71])
    : "l"(da), "l"(db), "r"(scale_d), "n"(TA));
}
template<int TA> __device__ __forceinline__ void wgmma72(float (&d)[36], uint64_t da, uint64_t db, int scale_d) {
  asm volatile("{\n.reg .pred p;\nsetp.ne.b32 p, %38, 0;\n"
    "wgmma.mma_async.sync.aligned.m64n72k16.f32.bf16.bf16 "
    "{%0, %1, %2, %3, %4, %5, %6, %7, %8, %9, %10, %11, "
    "%12, %13, %14, %15, %16, %17, %18, %19, %20, %21, %22, %23, "
    "%24, %25, %26, %27, %28, %29, %30, %31, %32, %33, %34, %35}, "
    "%36, %37, p, 1, 1, %39, 0;\n}\n"
    : "+f"(d[0]), "+f"(d[1]), "+f"(d[2]), "+f"(d[3]), "+f"(d[4]), "+f"(d[5]), "+f"(d[6]), "+f"(d[7]),
      "+f"(d[8]), "+f"(d[9]), "+f"(d[10]), "+f"(d[11]), "+f"(d[12]), "+f"(d[13]), "+f"(d[14]), "+f"(d[15]),
      "+f"(d[16]), "+f"(d[17]), "+f"(d[18]), "+f"(d[19]), "+f"(d[20]), "+f"(d[21]), "+f"(d[22]), "+f"(d[23]),
      "+f"(d[24]), "+f"(d[25]), "+f"(d[26]), "+f"(d[27]), "+f"(d[28]), "+f"(d[29]), "+f"(d[30]), "+f"(d[31]),
      "+f"(d[32]), "+f"(d[33]), "+f"(d[34]), "+f"(d[35])
    : "l"(da), "l"(db), "r"(scale_d), "n"(TA));
}

__device__ __forceinline__ void slow_item(uint32_t os, uint32_t qs, const __nv_bfloat16* __restrict__ X, const __nv_bfloat16* __restrict__ W,
                                          const __nv_bfloat16* __restrict__ K, const __nv_bfloat16* __restrict__ V, int warp, int lane) {
  for (int q = warp; q < SQ; q += 4) {
    {
      float q0 = 0.f, q1 = 0.f, q2 = 0.f, q3 = 0.f;
      for (int k = 0; k < DM; k++) {
        const float xv = __bfloat162float(X[q * DM + k]);
        const uint2 ww = *reinterpret_cast<const uint2*>(W + (size_t)k * (NH * DH) + lane * 4);
        q0 = fmaf(xv, __uint_as_float(ww.x << 16), q0); q1 = fmaf(xv, __uint_as_float(ww.x & 0xffff0000u), q1);
        q2 = fmaf(xv, __uint_as_float(ww.y << 16), q2); q3 = fmaf(xv, __uint_as_float(ww.y & 0xffff0000u), q3);
      }
      const float c = 0.08838834764831845f * 1.4426950408889634f;
      const uint32_t u0 = pack_bf16(q0 * c, q1 * c), u1 = pack_bf16(q2 * c, q3 * c);
      __syncwarp();
      asm volatile("st.shared.v4.f32 [%0], {%1, %2, %3, %4};" :: "r"(qs + lane * 16), "f"(__uint_as_float(u0 << 16)), "f"(__uint_as_float(u0 & 0xffff0000u)),
                   "f"(__uint_as_float(u1 << 16)), "f"(__uint_as_float(u1 & 0xffff0000u)) : "memory");
      __syncwarp();
    }
    float s[16];
    #pragma unroll
    for (int t = 0; t < 16; t++) s[t] = 0.f;
    for (int ch = 0; ch < 16; ch++) {
      float qf[8];
      asm volatile("ld.shared.v4.f32 {%0, %1, %2, %3}, [%4];" : "=f"(qf[0]), "=f"(qf[1]), "=f"(qf[2]), "=f"(qf[3]) : "r"(qs + ch * 32));
      asm volatile("ld.shared.v4.f32 {%0, %1, %2, %3}, [%4];" : "=f"(qf[4]), "=f"(qf[5]), "=f"(qf[6]), "=f"(qf[7]) : "r"(qs + ch * 32 + 16));
      #pragma unroll
      for (int t = 0; t < 16; t++) {
        const uint4 kk = *reinterpret_cast<const uint4*>(K + (size_t)(t * 32 + lane) * DH + ch * 8);
        s[t] = fmaf(qf[0], __uint_as_float(kk.x << 16), s[t]); s[t] = fmaf(qf[1], __uint_as_float(kk.x & 0xffff0000u), s[t]);
        s[t] = fmaf(qf[2], __uint_as_float(kk.y << 16), s[t]); s[t] = fmaf(qf[3], __uint_as_float(kk.y & 0xffff0000u), s[t]);
        s[t] = fmaf(qf[4], __uint_as_float(kk.z << 16), s[t]); s[t] = fmaf(qf[5], __uint_as_float(kk.z & 0xffff0000u), s[t]);
        s[t] = fmaf(qf[6], __uint_as_float(kk.w << 16), s[t]); s[t] = fmaf(qf[7], __uint_as_float(kk.w & 0xffff0000u), s[t]);
      }
    }
    float m = s[0];
    #pragma unroll
    for (int t = 1; t < 16; t++) m = fmaxf(m, s[t]);
    #pragma unroll
    for (int o = 16; o > 0; o >>= 1) m = fmaxf(m, __shfl_xor_sync(0xffffffffu, m, o));
    float l = 0.f;
    #pragma unroll
    for (int t = 0; t < 16; t++) { s[t] = exp2f(s[t] - m); l += s[t]; }
    #pragma unroll
    for (int o = 16; o > 0; o >>= 1) l += __shfl_xor_sync(0xffffffffu, l, o);
    float o0 = 0.f, o1 = 0.f, o2 = 0.f, o3 = 0.f;
    #pragma unroll
    for (int t = 0; t < 16; t++) {
      for (int src = 0; src < 32; src++) {
        const float p = __shfl_sync(0xffffffffu, s[t], src);
        const uint2 vv = *reinterpret_cast<const uint2*>(V + (size_t)(t * 32 + src) * DH + lane * 4);
        o0 = fmaf(p, __uint_as_float(vv.x << 16), o0); o1 = fmaf(p, __uint_as_float(vv.x & 0xffff0000u), o1);
        o2 = fmaf(p, __uint_as_float(vv.y << 16), o2); o3 = fmaf(p, __uint_as_float(vv.y & 0xffff0000u), o3);
      }
    }
    const float inv = 1.f / l;
    const uint32_t oa = os + (lane >> 4) * BT + q * 128 + ((((lane & 15) >> 1) ^ (q & 7)) << 4) + (lane & 1) * 8;
    asm volatile("st.shared.v2.u32 [%0], {%1, %2};" :: "r"(oa), "r"(pack_bf16(o0 * inv, o1 * inv)), "r"(pack_bf16(o2 * inv, o3 * inv)) : "memory");
  }
}

__device__ __forceinline__ void proj_chunk(float (&acc0)[72], float (&acc1)[72], uint32_t sb, uint32_t fullbar, uint32_t& phbits, uint32_t slot, int accumulate) {
  mbar_wait(fullbar + 8u * slot, (phbits >> slot) & 1);
  phbits ^= 1u << slot;
  const uint64_t db = make_desc(sb + aux_off(slot)), da = make_desc(sb + aux_off(slot) + BT);
  wgmma_fence();
  wgmma144<1>(acc0, da, db, accumulate);
  wgmma144<1>(acc1, da + (8192 >> 4), db, accumulate);
  #pragma unroll
  for (int ks = 1; ks < 4; ks++) {
    wgmma144<1>(acc0, da + ((ks * 2048) >> 4), db + ((ks * 32) >> 4), 1);
    wgmma144<1>(acc1, da + ((8192 + ks * 2048) >> 4), db + ((ks * 32) >> 4), 1);
  }
  wgmma_commit();
}

template<int PART> __device__ __forceinline__ void s_batch(float (&acc)[36], uint32_t ktile, uint32_t qhalf) {
  const uint64_t da = make_desc(ktile + PART * 8192), db = make_desc(qhalf + PART * BT);
  if (PART == 0) wgmma_fence();
  #pragma unroll
  for (int ks = 0; ks < 4; ks++) wgmma72<0>(acc, da + ((ks * 32) >> 4), db + ((ks * 32) >> 4), (PART | ks) != 0);
  wgmma_commit();
}
template<int PART> __device__ __forceinline__ void exp_part(float (&acc)[36], float* l, uint32_t pa) {
  #pragma unroll
  for (int ii = 2 * PART; ii < 2 * PART + 2; ii++) {
    float p[8];
    #pragma unroll
    for (int e = 0; e < 8; e++) p[e] = ex2(acc[8 * ii + e]);
    l[4 * ii + 0] += p[0] + p[2]; l[4 * ii + 1] += p[1] + p[3];
    l[4 * ii + 2] += p[4] + p[6]; l[4 * ii + 3] += p[5] + p[7];
    stsm_x4_t(pa + ii * 2048, pack_bf16(p[0], p[1]), pack_bf16(p[2], p[3]), pack_bf16(p[4], p[5]), pack_bf16(p[6], p[7]));
  }
  if (PART == 1) {
    float p[4];
    #pragma unroll
    for (int e = 0; e < 4; e++) p[e] = ex2(acc[32 + e]);
    l[16] += p[0] + p[2]; l[17] += p[1] + p[3];
    stsm_x2_t(pa + 4 * 2048, pack_bf16(p[0], p[1]), pack_bf16(p[2], p[3]));
  }
}

__device__ __forceinline__ void finish_out(float (&keep)[72], float (&send)[72], __nv_bfloat16* __restrict__ out, uint32_t sb, int g, int cb, int kh, int tid) {
  const int t = tid & 127, warp = (tid >> 5) & 3, lane = tid & 31;
  const uint32_t xbar = sb + OFF_BAR + 8u * B_X_FULL;
  {
    const uint32_t rdst = mapa(sb + OFF_KV + t * 16, 1 - kh), rbar = mapa(xbar, 1 - kh);
    #pragma unroll
    for (int i = 0; i < 18; i++) st_async_v4(rdst + i * 2048, send[4 * i], send[4 * i + 1], send[4 * i + 2], send[4 * i + 3], rbar);
  }
  if (FINE_ITEM == 4) FINE(132);
  mbar_wait_cluster(xbar, 0);
  if (FINE_ITEM == 4) FINE(133);
  PROF(3, 20);
  const uint32_t st_off = (uint32_t)((8 * (lane >> 4) + (lane & 7)) * 128 + (((2 * warp + ((lane >> 3) & 1)) ^ (lane & 7)) << 4));
  const uint32_t stage = sb + OFF_AUX;
  #pragma unroll
  for (int ii = 0; ii < 9; ii++) {
    float4 u, v;
    asm volatile("ld.shared.v4.f32 {%0, %1, %2, %3}, [%4];" : "=f"(u.x), "=f"(u.y), "=f"(u.z), "=f"(u.w) : "r"(sb + OFF_KV + t * 16 + (2 * ii) * 2048));
    asm volatile("ld.shared.v4.f32 {%0, %1, %2, %3}, [%4];" : "=f"(v.x), "=f"(v.y), "=f"(v.z), "=f"(v.w) : "r"(sb + OFF_KV + t * 16 + (2 * ii + 1) * 2048));
    stsm_x4_t(stage + st_off + ii * 2048, pack_bf16(keep[8 * ii] + u.x, keep[8 * ii + 1] + u.y), pack_bf16(keep[8 * ii + 2] + u.z, keep[8 * ii + 3] + u.w),
              pack_bf16(keep[8 * ii + 4] + v.x, keep[8 * ii + 5] + v.y), pack_bf16(keep[8 * ii + 6] + v.z, keep[8 * ii + 7] + v.w));
  }
  named_bar(3, 128);
  {
    __nv_bfloat16* op = out + (size_t)((g & 7) * SQ) * (2 * DM) + (g >> 3) * 512 + cb * 128 + kh * 64;
    const int ch = t & 7;
    #pragma unroll
    for (int r = 0; r < 9; r++) {
      const int row = r * 16 + (t >> 3);
      uint4 v;
      asm volatile("ld.shared.v4.u32 {%0, %1, %2, %3}, [%4];" : "=r"(v.x), "=r"(v.y), "=r"(v.z), "=r"(v.w) : "r"(stage + row * 128 + ((ch ^ (row & 7)) << 4)));
      *reinterpret_cast<uint4*>(op + (size_t)row * (2 * DM) + ch * 8) = v;
    }
  }
}

__global__ void __cluster_dims__(2, 1, 1) __launch_bounds__(NTHREADS, 1)
fused_kernel(const __grid_constant__ Params prm, const __grid_constant__ RawPtrs raw) {
  extern __shared__ __align__(1024) unsigned char smem[];
  const uint32_t sb = smem_u32(smem);
  const int tid = threadIdx.x, wg = tid >> 7, warp = (tid >> 5) & 3, lane = tid & 31;
  int g, j;
  { const int c = blockIdx.x >> 1; int mem;
    if (c < 4) { g = 15; mem = c; }
    else if (c < 36) { g = (c - 4) & 7; mem = (c - 4) >> 3; }
    else { g = 8 + (c - 36) % 7; mem = (c - 36) / 7; }
    j = 2 * mem + (blockIdx.x & 1); }
  const int br = g >> 3, b = g & 7;
  const int cb = j >> 1, kh = j & 1;
  const uint32_t bar = sb + OFF_BAR;
  auto BAR = [&](int i) { return bar + 8u * i; };

  if (tid == 0) {
    if (sb & 1023) __trap();
    prefetch2d(&prm.x[br], j * 64, b * SQ);
    prefetch3d(&prm.wq[br], 0, b * 64, 2 * j);
    for (int i = 0; i < NKV; i++) { mbar_init(BAR(B_K_FULL + i), 1); mbar_init(BAR(B_V_FULL + i), 1); mbar_init(BAR(B_KV_EMPTY + i), 4); }
    for (int i = 0; i < 4; i++) { mbar_init(BAR(B_AUXQ_FULL + i), 1); mbar_init(BAR(B_AUXO_FULL + i), 1); mbar_init(BAR(B_AUX_EMPTY + i), 4); }
    for (int i = 0; i < NP; i++) { mbar_init(BAR(B_P_FULL + i), 4); mbar_init(BAR(B_P_EMPTY + i), 4); }
    mbar_init(BAR(B_Q_FULL), 4); mbar_init(BAR(B_QA_FULL), 4); mbar_init(BAR(B_O_FREE), 1); mbar_init(BAR(B_QLD), 4); mbar_init(BAR(B_L_FULL), 4); mbar_init(BAR(B_O_STAGED), 4);
    for (int i = 0; i < 8; i++) mbar_init(BAR(B_PV_DONE + i), 4);
    for (int i = 0; i < 3; i++) mbar_init(BAR(B_FREEQ + i), 4);
    for (int i = 0; i < 4; i++) *reinterpret_cast<volatile uint32_t*>(smem + OFF_BAD + 4 * i) = 0;
    *reinterpret_cast<volatile uint32_t*>(smem + OFF_EPOCH) = *reinterpret_cast<volatile unsigned*>(&g_epoch);
    mbar_init(BAR(B_X_FULL), 1);
    asm volatile("fence.mbarrier_init.release.cluster;" ::: "memory");
    mbar_expect_tx(BAR(B_X_FULL), 18 * 128 * 16);
  }
  __syncthreads();
  asm volatile("barrier.cluster.arrive.relaxed.aligned;" ::: "memory");

  if (wg == 0) {
    asm volatile("setmaxnreg.dec.sync.aligned.u32 %0;" :: "n"(REG_PROD));
    const unsigned epoch = *reinterpret_cast<volatile uint32_t*>(smem + OFF_EPOCH);
    if (warp == 0 && lane == 0) {
      uint64_t pol; asm volatile("createpolicy.fractional.L2::evict_first.b64 %0, 1.0;" : "=l"(pol));
      const CUtensorMap* tk = &prm.k[br];
      const CUtensorMap* tv = &prm.v[br];
      uint32_t slot = 0, ph = 1;
      uint32_t fb1 = 0, fb2 = 0, fp1 = 0, fp2 = 0, kph = 0, vph = 0;
      #pragma unroll 1
      for (int i = 0; i < 4; i++) {
        const int row0 = ((b * NH) + 8 * i + j) * SK;
        #pragma unroll 1
        for (int t = 0; t < 16; t++) {
          const bool isv = (t == 15) || (t >= 2 && !(t & 1));
          const int idx = (t == 15) ? 7 : (isv ? (t >> 1) - 1 : (t + 1) >> 1);
          mbar_wait(BAR(B_KV_EMPTY + slot), ph);
          if (t < KVSLOW) { if (KVFLIGHT == 1) { if (fb1) mbar_wait(fb1, fp1); } else if (fb2) mbar_wait(fb2, fp2); }
          const uint32_t fb = BAR((isv ? B_V_FULL : B_K_FULL) + slot);
          mbar_expect_tx(fb, AT);
          tma3d_hint(sb + OFF_KV + slot * AT, isv ? tv : tk, 0, row0 + idx * 64, 0, fb, pol);
          fb2 = fb1; fp2 = fp1; fb1 = fb;
          if (isv) { fp1 = (vph >> slot) & 1; vph ^= 1u << slot; } else { fp1 = (kph >> slot) & 1; kph ^= 1u << slot; }
          if (++slot == NKV) { slot = 0; ph ^= 1; }
        }
        PROFT(0, i);
      }
    } else if (warp == 1 && lane == 0) {
      uint32_t eph = 0;
      auto o_chunks = [&](int w) {
        const unsigned* fl = &g_flagO[g * 32 + 8 * w + 4 * (1 - kh)];
        uint32_t ready = 0;
        const int npre = (w == 3) ? 3 : 0;
        auto arm = [&](int c) {
          const uint32_t slot = (w == 3) ? wide_slot(c) : (c & 1);
          mbar_wait(BAR(B_AUX_EMPTY + slot), (eph >> slot) & 1);
          eph ^= 1u << slot;
          const uint32_t fb = BAR(B_AUXO_FULL + slot);
          mbar_expect_tx(fb, AUX_SLOT);
          tma3d(sb + aux_off(slot) + BT, &prm.wo[br], 0, (8 * w + 2 * (c >> 1) + (1 - kh)) * DH + (c & 1) * 64, 2 * cb, fb);
        };
        for (int c = 0; c < npre; c++) arm(c);
        for (int c = 0; c < 8; c++) {
          const int jj = 2 * (c >> 1) + (1 - kh);
          const uint32_t slot = (w == 3) ? wide_slot(c) : (c & 1);
          if (c >= npre) arm(c);
          if (!((ready >> (c >> 1)) & 1)) { uint32_t n = 0; while (!(((ready = poll_flags4(fl, epoch + 1)) >> (c >> 1)) & 1)) { WAIT_TIMEOUT(n, 0x1000) } CONS_FENCE(); }
          bulk_g2s(sb + aux_off(slot), g_O + (size_t)((((w % OBUF) * 16 + g) * 8 + jj) * 2 + (c & 1)) * BT, BT, BAR(B_AUXO_FULL + slot));
        }
      };
      #pragma unroll 1
      for (int w = 0; w < 4; w++) { o_chunks(w); PROFT(0, 9 + w); }
    } else if (warp == 2 && lane == 0) {
      if (atomicAdd(&g_done, 1) == NCTA - 1) { g_done = 0; __threadfence(); *reinterpret_cast<volatile unsigned*>(&g_epoch) = epoch + 1; }
      for (int i = 0; i < 4; i++) {
        if (i >= OBUF) wait_flag_eq(&g_cons[(g * 2 + (1 - kh)) * 4 + (i - OBUF)], (epoch + 1) * 4);
        mbar_wait(BAR(B_O_STAGED), i & 1);
        if (i < 3) mbar_wait(BAR(B_QLD), (i + 1) & 1);
        bulk_s2g(g_O + (size_t)(((i % OBUF) * 16 + g) * 8 + j) * 2 * BT, sb + OFF_P, 2 * BT);
        bulk_commit();
        bulk_wait_read();
        if (i < 3) mbar_arrive(BAR(B_O_FREE)); else mbar_arrive_n(BAR(B_AUX_EMPTY + 3), 4);
        bulk_wait_all();
        st_relaxed(&g_flagO[g * 32 + 8 * i + 4 * kh + cb], epoch + 1);
        PROFT(0, 16 + i);
      }
    } else if (warp == 3 && lane == 0) {
      uint32_t qph = 0x7;
      #pragma unroll 1
      for (int i = 0; i < 4; i++) {
        #pragma unroll 1
        for (int kc = 0; kc < 8; kc++) {
          const uint32_t slot = q_slot(kc);
          mbar_wait(BAR(B_FREEQ + slot), (qph >> slot) & 1);
          qph ^= 1u << slot;
          const uint32_t dst = sb + aux_off(slot), fb = BAR(B_AUXQ_FULL + slot);
          mbar_expect_tx(fb, AUX_SLOT);
          tma2d(dst, &prm.x[br], kc * 64, b * SQ, fb);
          tma3d(dst + BT, &prm.wq[br], 0, kc * 64, 2 * (8 * i + j), fb);
        }
        if (i < 3) prefetch3d(&prm.wq[br], 0, b * 64, 2 * (8 * (i + 1) + j));
        prefetch3d(&prm.wo[br], 0, (8 * i + 2 * (b >> 1) + (1 - kh)) * DH + (b & 1) * 64, 2 * cb);
      }
    }
  } else if (wg == 1) {
    if constexpr (REG_S > 128) asm volatile("setmaxnreg.inc.sync.aligned.u32 %0;" :: "n"(REG_S));
    const uint32_t st_off = (uint32_t)((8 * (lane >> 4) + (lane & 7)) * 128 + (((2 * warp + ((lane >> 3) & 1)) ^ (lane & 7)) << 4));
    float sa[36], sc[36];
    uint32_t kph = 0;
    for (int i = 0; i < 4; i++) {
      float l[36];
      #pragma unroll
      for (int c = 0; c < 36; c++) l[c] = 0.f;
      uint32_t slot = (16 * i) % NKV;
      mbar_wait(BAR(B_K_FULL + slot), (kph >> slot) & 1);
      kph ^= 1u << slot;
      mbar_wait(BAR(B_QA_FULL), i & 1);
      PROF(1, 16 * i);
      s_batch<0>(sa, sb + OFF_KV + slot * AT, sb + OFF_Q);
      s_batch<1>(sa, sb + OFF_KV + slot * AT, sb + OFF_Q);
      mbar_wait(BAR(B_Q_FULL), i & 1);
      s_batch<0>(sc, sb + OFF_KV + slot * AT, sb + OFF_Q + 9216);
      if (i > 0) mbar_wait(BAR(B_O_FREE), (i - 1) & 1);
      #pragma unroll 1
      for (int jt = 0; jt < 7; jt++) {
        const int m = 8 * i + jt;
        const uint32_t pa = sb + OFF_P + (m & 1) * BT + st_off;
        const uint32_t nslot = (16 * i + 2 * jt + 1) % NKV;
        const uint32_t kt = sb + OFF_KV + slot * AT, kn = sb + OFF_KV + nslot * AT;
        wgmma_wait<1>();
        fence_regs(sa);
        if (i == FINE_ITEM) FINE(jt * 4 + 0);
        s_batch<1>(sc, kt, sb + OFF_Q + 9216);
        mbar_wait(BAR(B_P_EMPTY + (m & 1)), ((m >> 1) & 1) ^ 1);
        exp_part<0>(sa, l, pa);
        wgmma_wait<0>();
        fence_regs(sc);
        if (lane == 0) mbar_arrive(BAR(B_KV_EMPTY + slot));
        exp_part<1>(sa, l, pa);
        if (i == FINE_ITEM) FINE(jt * 4 + 1);
        mbar_wait(BAR(B_K_FULL + nslot), (kph >> nslot) & 1);
        kph ^= 1u << nslot;
        s_batch<0>(sa, kn, sb + OFF_Q);
        if (i == FINE_ITEM) FINE(jt * 4 + 2);
        exp_part<0>(sc, l + 18, pa + 9216);
        s_batch<1>(sa, kn, sb + OFF_Q);
        exp_part<1>(sc, l + 18, pa + 9216);
        fence_proxy_async();
        __syncwarp();
        if (lane == 0) mbar_arrive(BAR(B_P_FULL + (m & 1)));
        if (i == FINE_ITEM) FINE(jt * 4 + 3);
        s_batch<0>(sc, kn, sb + OFF_Q + 9216);
        slot = nslot;
        PROF(1, 16 * i + 1 + jt);
      }
      {
        const int m = 8 * i + 7;
        const uint32_t pa = sb + OFF_P + (m & 1) * BT + st_off;
        wgmma_wait<1>();
        fence_regs(sa);
        s_batch<1>(sc, sb + OFF_KV + slot * AT, sb + OFF_Q + 9216);
        mbar_wait(BAR(B_P_EMPTY + (m & 1)), ((m >> 1) & 1) ^ 1);
        exp_part<0>(sa, l, pa);
        exp_part<1>(sa, l, pa);
        wgmma_wait<0>();
        fence_regs(sc);
        if (lane == 0) { mbar_arrive(BAR(B_KV_EMPTY + slot)); mbar_arrive(BAR((i < 3 ? B_FREEQ : B_AUX_EMPTY) + 2)); }
        exp_part<0>(sc, l + 18, pa + 9216);
        exp_part<1>(sc, l + 18, pa + 9216);
        fence_proxy_async();
        __syncwarp();
        if (lane == 0) mbar_arrive(BAR(B_P_FULL + (m & 1)));
        PROF(1, 16 * i + 8);
      }
      {
        const bool b4 = lane & 16, b3 = lane & 8, b2 = lane & 4;
        float m1[18], m2[9], m3[5];
        #pragma unroll
        for (int k = 0; k < 18; k++) m1[k] = (b4 ? l[18 + k] : l[k]) + __shfl_xor_sync(0xffffffffu, b4 ? l[k] : l[18 + k], 16);
        #pragma unroll
        for (int k = 0; k < 9; k++) m2[k] = (b3 ? m1[9 + k] : m1[k]) + __shfl_xor_sync(0xffffffffu, b3 ? m1[k] : m1[9 + k], 8);
        #pragma unroll
        for (int k = 0; k < 5; k++) {
          const float hi = (k < 4) ? m2[5 + (k < 4 ? k : 0)] : 0.f;
          m3[k] = (b2 ? hi : m2[k]) + __shfl_xor_sync(0xffffffffu, b2 ? m2[k] : hi, 4);
        }
        float* lred = reinterpret_cast<float*>(smem + OFF_LRED) + warp * SQ + 2 * (lane & 3);
        const int base = (b4 ? 18 : 0) + (b3 ? 9 : 0) + (b2 ? 5 : 0);
        #pragma unroll
        for (int k = 0; k < 5; k++) if (k < 4 || !b2) lred[8 * ((base + k) >> 1) + ((base + k) & 1)] = m3[k];
      }
      named_bar(1, 128);
      {
        const float* lred = reinterpret_cast<const float*>(smem + OFF_LRED);
        float* invl = reinterpret_cast<float*>(smem + OFF_INVL);
        const int t = tid & 127;
        #pragma unroll
        for (int r = 0; r < 2; r++) {
          const int q = t + 128 * r;
          if (q < SQ) {
            const float s = (lred[q] + lred[SQ + q]) + (lred[2 * SQ + q] + lred[3 * SQ + q]);
            invl[q] = __frcp_rn(s);
            if (!(s >= 9.5367431640625e-7f && s <= 1.152921504606847e18f)) *reinterpret_cast<volatile uint32_t*>(smem + OFF_BAD + 4 * i) = 1;
          }
        }
      }
      __syncwarp();
      if (lane == 0) mbar_arrive(BAR(B_L_FULL));
      PROF(1, 16 * i + 9);
    }
  } else {
    asm volatile("setmaxnreg.inc.sync.aligned.u32 %0;" :: "n"(REG_O));
    float acc0[72], acc1[72];
    if (wg == 2) {
    const uint32_t st_off = (uint32_t)((8 * (lane >> 4) + (lane & 7)) * 128 + (((2 * warp + ((lane >> 3) & 1)) ^ (lane & 7)) << 4));
    uint32_t aph = 0, vph = 0;
    for (int i = 0; i < 4; i++) {
      PROF(2, 16 * i);
      if (i == FINE_ITEM) FINE(127);
      proj_chunk(acc0, acc1, sb, BAR(B_AUXQ_FULL), aph, q_slot(0), 0);
      if (i == FINE_ITEM) FINE(128);
      #pragma unroll 1
      for (int kc = 1; kc < 8; kc++) {
        proj_chunk(acc0, acc1, sb, BAR(B_AUXQ_FULL), aph, q_slot(kc), 1);
        if (kc == QLD_AT && lane == 0) mbar_arrive(BAR(B_QLD));
        if (i == FINE_ITEM) FINE(128 + kc);
        wgmma_wait<1>();
        if (lane == 0 && kc != 7) mbar_arrive(BAR(((kc == 6 && i > 0) ? B_AUX_EMPTY : B_FREEQ) + q_slot(kc - 1)));
      }
      wgmma_wait<0>();
      fence_regs(acc0); fence_regs(acc1);
      if (i == FINE_ITEM) FINE(136);
      if (lane == 0) mbar_arrive(BAR((i > 0 ? B_AUX_EMPTY : B_FREEQ) + q_slot(7)));
      {
        const float c = 0.08838834764831845f * 1.4426950408889634f;
        #pragma unroll
        for (int ii = 0; ii < 4; ii++) {
          stsm_x4_t(sb + OFF_Q + st_off + ii * 2048, pack_bf16(acc0[8 * ii] * c, acc0[8 * ii + 1] * c), pack_bf16(acc0[8 * ii + 2] * c, acc0[8 * ii + 3] * c),
                    pack_bf16(acc0[8 * ii + 4] * c, acc0[8 * ii + 5] * c), pack_bf16(acc0[8 * ii + 6] * c, acc0[8 * ii + 7] * c));
          stsm_x4_t(sb + OFF_Q + BT + st_off + ii * 2048, pack_bf16(acc1[8 * ii] * c, acc1[8 * ii + 1] * c), pack_bf16(acc1[8 * ii + 2] * c, acc1[8 * ii + 3] * c),
                    pack_bf16(acc1[8 * ii + 4] * c, acc1[8 * ii + 5] * c), pack_bf16(acc1[8 * ii + 6] * c, acc1[8 * ii + 7] * c));
        }
        stsm_x2_t(sb + OFF_Q + st_off + 4 * 2048, pack_bf16(acc0[32] * c, acc0[33] * c), pack_bf16(acc0[34] * c, acc0[35] * c));
        stsm_x2_t(sb + OFF_Q + BT + st_off + 4 * 2048, pack_bf16(acc1[32] * c, acc1[33] * c), pack_bf16(acc1[34] * c, acc1[35] * c));
        fence_proxy_async();
        __syncwarp();
        if (lane == 0) mbar_arrive(BAR(B_QA_FULL));
        #pragma unroll
        for (int ii = 0; ii < 4; ii++) {
          stsm_x4_t(sb + OFF_Q + 9216 + st_off + ii * 2048, pack_bf16(acc0[36 + 8 * ii] * c, acc0[36 + 8 * ii + 1] * c), pack_bf16(acc0[36 + 8 * ii + 2] * c, acc0[36 + 8 * ii + 3] * c),
                    pack_bf16(acc0[36 + 8 * ii + 4] * c, acc0[36 + 8 * ii + 5] * c), pack_bf16(acc0[36 + 8 * ii + 6] * c, acc0[36 + 8 * ii + 7] * c));
          stsm_x4_t(sb + OFF_Q + BT + 9216 + st_off + ii * 2048, pack_bf16(acc1[36 + 8 * ii] * c, acc1[36 + 8 * ii + 1] * c), pack_bf16(acc1[36 + 8 * ii + 2] * c, acc1[36 + 8 * ii + 3] * c),
                    pack_bf16(acc1[36 + 8 * ii + 4] * c, acc1[36 + 8 * ii + 5] * c), pack_bf16(acc1[36 + 8 * ii + 6] * c, acc1[36 + 8 * ii + 7] * c));
        }
        stsm_x2_t(sb + OFF_Q + 9216 + st_off + 4 * 2048, pack_bf16(acc0[68] * c, acc0[69] * c), pack_bf16(acc0[70] * c, acc0[71] * c));
        stsm_x2_t(sb + OFF_Q + BT + 9216 + st_off + 4 * 2048, pack_bf16(acc1[68] * c, acc1[69] * c), pack_bf16(acc1[70] * c, acc1[71] * c));
      }
      if (i == FINE_ITEM) FINE(137);
      fence_proxy_async();
      if (i == FINE_ITEM) FINE(138);
      __syncwarp();
      if (lane == 0) mbar_arrive(BAR(B_Q_FULL));
      PROF(2, 16 * i + 1);
      #pragma unroll 1
      for (int jt = 0; jt < 8; jt++) {
        const int n = 16 * i + (jt == 7 ? 15 : 2 * jt + 2);
        const uint32_t slot = n % NKV;
        const int m = 8 * i + jt;
        mbar_wait(BAR(B_V_FULL + slot), (vph >> slot) & 1);
        vph ^= 1u << slot;
        if (i == FINE_ITEM) FINE(64 + jt * 4 + 0);
        mbar_wait(BAR(B_P_FULL + (m & 1)), (m >> 1) & 1);
        if (i == FINE_ITEM) FINE(64 + jt * 4 + 1);
        const uint64_t da = make_desc(sb + OFF_KV + slot * AT), db = make_desc(sb + OFF_P + (m & 1) * BT);
        wgmma_fence();
        #pragma unroll
        for (int ks = 0; ks < 4; ks++) {
          wgmma144<1>(acc0, da + ((ks * 2048) >> 4), db + ((ks * 32) >> 4), (jt | ks) != 0);
          wgmma144<1>(acc1, da + ((8192 + ks * 2048) >> 4), db + ((ks * 32) >> 4), (jt | ks) != 0);
        }
        wgmma_commit();
        wgmma_wait<0>();
        if (i == FINE_ITEM) FINE(64 + jt * 4 + 2);
        if (lane == 0) { mbar_arrive(BAR(B_P_EMPTY + (m & 1))); mbar_arrive(BAR(B_KV_EMPTY + slot)); mbar_arrive(BAR(B_PV_DONE + jt)); }
        PROF(2, 16 * i + 2 + jt);
      }
      fence_regs(acc0); fence_regs(acc1);
      if (i == FINE_ITEM) FINE(180);
      mbar_wait(BAR(B_L_FULL), i & 1);
      if (i == FINE_ITEM) FINE(181);
      const float* invl = reinterpret_cast<const float*>(smem + OFF_INVL) + 2 * (lane & 3);
      uint32_t chk = 0;
      #pragma unroll
      for (int ii = 0; ii < 9; ii++) {
        const float2 iv = *reinterpret_cast<const float2*>(invl + 16 * ii), iw = *reinterpret_cast<const float2*>(invl + 16 * ii + 8);
        uint32_t r0 = pack_bf16(acc0[8 * ii] * iv.x, acc0[8 * ii + 1] * iv.y), r1 = pack_bf16(acc0[8 * ii + 2] * iv.x, acc0[8 * ii + 3] * iv.y);
        uint32_t r2 = pack_bf16(acc0[8 * ii + 4] * iw.x, acc0[8 * ii + 5] * iw.y), r3 = pack_bf16(acc0[8 * ii + 6] * iw.x, acc0[8 * ii + 7] * iw.y);
        chk = bf16x2_chk(r0, r1, chk); chk = bf16x2_chk(r2, r3, chk);
        stsm_x4_t(sb + OFF_P + st_off + ii * 2048, r0, r1, r2, r3);
        r0 = pack_bf16(acc1[8 * ii] * iv.x, acc1[8 * ii + 1] * iv.y); r1 = pack_bf16(acc1[8 * ii + 2] * iv.x, acc1[8 * ii + 3] * iv.y);
        r2 = pack_bf16(acc1[8 * ii + 4] * iw.x, acc1[8 * ii + 5] * iw.y); r3 = pack_bf16(acc1[8 * ii + 6] * iw.x, acc1[8 * ii + 7] * iw.y);
        chk = bf16x2_chk(r0, r1, chk); chk = bf16x2_chk(r2, r3, chk);
        stsm_x4_t(sb + OFF_P + BT + st_off + ii * 2048, r0, r1, r2, r3);
      }
      if (i == FINE_ITEM) FINE(182);
      const bool bad = ((chk & 0x7f80u) == 0x7f80u) || ((chk & 0x7f800000u) == 0x7f800000u) || (*reinterpret_cast<volatile uint32_t*>(smem + OFF_BAD + 4 * i) != 0);
      if (named_bar_or(2, 128, bad)) {
        const size_t off = (size_t)((b * NH) + 8 * i + j) * SK * DH;
        slow_item(sb + OFF_P, sb + OFF_LRED + warp * 576, raw.x[br] + b * SQ * DM, raw.wq[br] + (8 * i + j) * DH, raw.k[br] + off, raw.v[br] + off, warp, lane);
      }
      if (i == FINE_ITEM) FINE(183);
      fence_proxy_async();
      __syncwarp();
      if (lane == 0) mbar_arrive(BAR(B_O_STAGED));
      if (i == FINE_ITEM) FINE(184);
      PROF(2, 16 * i + 10);
    }
    } else {
    asm volatile("barrier.cluster.wait.acquire.aligned;" ::: "memory");
    PROF(3, 0);
    uint32_t aph = 0;
    proj_chunk(acc0, acc1, sb, BAR(B_AUXO_FULL), aph, 0, 0);
    #pragma unroll 1
    for (int c = 1; c < 32; c++) {
      const uint32_t slot = (c >= 24) ? wide_slot(c & 7) : (c & 1);
      if ((c & 7) == 0) {
        wgmma_wait<0>();
        if (lane == 0) mbar_arrive(BAR((c < 24 ? B_FREEQ : B_AUX_EMPTY) + 1));
        named_bar(3, 128);
        if ((tid & 127) == 0) red_release_add(&g_cons[(g * 2 + kh) * 4 + (c >> 3) - 1], 1);
        PROF(3, 4 * (c >> 3));
        proj_chunk(acc0, acc1, sb, BAR(B_AUXO_FULL), aph, slot, 1);
        if ((c >> 3) == FINE_ITEM - 1) FINE(160);
      } else {
        proj_chunk(acc0, acc1, sb, BAR(B_AUXO_FULL), aph, slot, 1);
        if ((c >> 3) == FINE_ITEM - 1) FINE(160 + (c & 7));
        wgmma_wait<1>();
        if (lane == 0) { if (c <= 24) mbar_arrive(BAR((((c & 7) == 7 && c < 16) ? B_FREEQ : B_AUX_EMPTY) + ((c - 1) & 1))); else if (wide_release((c - 1) & 7)) mbar_arrive(BAR(B_AUX_EMPTY + wide_slot((c - 1) & 7))); }
      }
    }
    wgmma_wait<0>();
    if ((tid & 127) == 0) red_release_add(&g_cons[(g * 2 + kh) * 4 + 3], 1);
    fence_regs(acc0); fence_regs(acc1);
    if (FINE_ITEM == 4) FINE(131);
    PROF(3, 19);
    if (kh == 0) finish_out(acc0, acc1, raw.out, sb, g, cb, 0, tid);
    else finish_out(acc1, acc0, raw.out, sb, g, cb, 1, tid);
    }
  }
}

typedef CUresult (*EncodeFn)(CUtensorMap*, CUtensorMapDataType, cuuint32_t, void*, const cuuint64_t*, const cuuint64_t*, const cuuint32_t*, const cuuint32_t*,
                             CUtensorMapInterleave, CUtensorMapSwizzle, CUtensorMapL2promotion, CUtensorMapFloatOOBfill);

bool encode(EncodeFn fn, CUtensorMap* m, void* p, int rank, const cuuint64_t* dims, const cuuint64_t* strides, const cuuint32_t* box,
            CUtensorMapL2promotion promo = CFG_PROMO) {
  const cuuint32_t es[3] = {1, 1, 1};
  return fn(m, CU_TENSOR_MAP_DATA_TYPE_BFLOAT16, rank, p, dims, strides, box, es, CU_TENSOR_MAP_INTERLEAVE_NONE, CU_TENSOR_MAP_SWIZZLE_128B,
            promo, CU_TENSOR_MAP_FLOAT_OOB_FILL_NONE) == CUDA_SUCCESS;
}

}

extern "C" void kernel_launch(void* const* d_in, const int* in_sizes, int n_in, void* d_out, int out_size) {
  (void)in_sizes; (void)n_in; (void)out_size;
  static Params prm;
  static void* cached[11] = {};
  static bool ok = false;
  bool same = ok && cached[10] == d_out;
  for (int i = 0; i < 10 && same; i++) same = cached[i] == d_in[i];
  if (!same) {
    void* fp = nullptr;
    cudaDriverEntryPointQueryResult qr;
    if (cudaGetDriverEntryPoint("cuTensorMapEncodeTiled", &fp, cudaEnableDefault, &qr) != cudaSuccess || !fp) return;
    EncodeFn fn = (EncodeFn)fp;
    bool good = true;
    for (int s = 0; s < 2; s++) {
      void* x = d_in[5 * s + 0]; void* k = d_in[5 * s + 1]; void* v = d_in[5 * s + 2]; void* wq = d_in[5 * s + 3]; void* wo = d_in[5 * s + 4];
      { cuuint64_t d[2] = {DM, NB * SQ}, st[1] = {DM * 2}; cuuint32_t bx[2] = {64, SQ}; good &= encode(fn, &prm.x[s], x, 2, d, st, bx); }
      { cuuint64_t d[3] = {64, DM, NH * DH / 64}, st[2] = {NH * DH * 2, 128}; cuuint32_t bx[3] = {64, 64, 2}; good &= encode(fn, &prm.wq[s], wq, 3, d, st, bx); }
      { cuuint64_t d[3] = {64, (cuuint64_t)NB * NH * SK, 2}, st[2] = {DH * 2, 128}; cuuint32_t bx[3] = {64, 64, 2};
        good &= encode(fn, &prm.k[s], k, 3, d, st, bx, CFG_PROMO_KV); good &= encode(fn, &prm.v[s], v, 3, d, st, bx, CFG_PROMO_KV); }
      { cuuint64_t d[3] = {64, NH * DH, DM / 64}, st[2] = {DM * 2, 128}; cuuint32_t bx[3] = {64, 64, 2}; good &= encode(fn, &prm.wo[s], wo, 3, d, st, bx); }
    }
    if (!good) return;
    cudaFuncSetAttribute(fused_kernel, cudaFuncAttributeMaxDynamicSharedMemorySize, SMEM_BYTES);
    for (int i = 0; i < 10; i++) cached[i] = d_in[i];
    cached[10] = d_out;
    ok = true;
  }
  RawPtrs raw;
  raw.out = (__nv_bfloat16*)d_out;
  for (int s = 0; s < 2; s++) {
    raw.x[s] = (const __nv_bfloat16*)d_in[5 * s + 0]; raw.k[s] = (const __nv_bfloat16*)d_in[5 * s + 1];
    raw.v[s] = (const __nv_bfloat16*)d_in[5 * s + 2]; raw.wq[s] = (const __nv_bfloat16*)d_in[5 * s + 3];
  }
  fused_kernel<<<NCTA, NTHREADS, SMEM_BYTES, cudaStreamPerThread>>>(prm, raw);
}
```

```cpp
#include <cuda_runtime.h>
#include <cuda_bf16.h>
#include <cuda.h>
#include <stdint.h>

namespace {

constexpr int SQ = 144, DM = 512, NH = 32, SK = 512, DH = 128, NB = 8;
constexpr int NCTA = 128;
constexpr int NTHREADS = 512;

constexpr int NP = 2;
constexpr int NAUX = 2;
constexpr int NKV = 5;
constexpr int KVPF = 3, KVPF0 = 5;
constexpr int REG_PROD = 24, REG_S = 136, REG_O = 176;
static_assert(REG_PROD + REG_S + 2 * REG_O <= 512, "regs");

constexpr uint32_t BT = SQ * 128;
constexpr uint32_t AT = 16384;
constexpr uint32_t AUX_SLOT = BT + AT;
constexpr uint32_t OFF_Q = 0;
constexpr uint32_t OFF_P = 2 * BT;
constexpr uint32_t OFF_AUX = OFF_P + NP * BT;
constexpr uint32_t OFF_KV = OFF_AUX + NAUX * AUX_SLOT;
constexpr uint32_t OFF_MISC = OFF_KV + NKV * AT;
constexpr uint32_t OFF_BAR = OFF_MISC;
constexpr uint32_t OFF_INVL = OFF_BAR + 512;
constexpr uint32_t OFF_LRED = OFF_INVL + 576;
constexpr uint32_t OFF_BAD = OFF_LRED + 2304;
constexpr uint32_t OFF_EPOCH = OFF_BAD + 16;
constexpr uint32_t SMEM_BYTES = OFF_BAD + 64;
static_assert(SMEM_BYTES <= 232448, "smem");

constexpr int B_K_FULL = 0, B_V_FULL = 8, B_KV_EMPTY = 16, B_AUXQ_FULL = 24, B_AUXO_FULL = 28, B_AUX_EMPTY = 32, B_P_FULL = 36, B_P_EMPTY = 38,
              B_Q_FULL = 40, B_L_FULL = 41, B_O_STAGED = 42, B_X_FULL = 43, B_QA_FULL = 44, B_O_FREE = 45, B_QLD = 46, B_EPOCH = 47,
              B_FREEQ = 48  ;
static_assert(NKV <= 8 && NAUX == 2 && NP == 2, "barrier table");

__host__ __device__ constexpr uint32_t aux_off(uint32_t s) { return s < 2 ? OFF_AUX + s * AUX_SLOT : (s == 2 ? OFF_Q : OFF_P); }

__host__ __device__ constexpr uint32_t wide_slot(uint32_t k) { return (0x02310210u >> (4 * k)) & 3u; }
__host__ __device__ constexpr bool wide_release(uint32_t k) { return k != 5 && k != 6; }

__host__ __device__ constexpr uint32_t q_slot_i(int i, uint32_t k) { return ((i == 0 ? 0x31023102u : 0x02102102u) >> (4 * k)) & 3u; }

struct Params {
  CUtensorMap x[2], wq[2], k[2], v[2], wo[2];
};

struct RawPtrs { const __nv_bfloat16 *x[2], *wq[2], *k[2], *v[2]; __nv_bfloat16* out; };

__device__ __align__(1024) unsigned char g_O[4 * 16 * 8 * 2 * BT];
__device__ __align__(16) unsigned g_flagO[16 * 32];
__device__ unsigned g_epoch;
__device__ unsigned g_done;

__device__ __forceinline__ uint32_t smem_u32(const void* p) { return (uint32_t)__cvta_generic_to_shared(p); }
__device__ __forceinline__ void mbar_init(uint32_t bar, uint32_t cnt) { asm volatile("mbarrier.init.shared::cta.b64 [%0], %1;" :: "r"(bar), "r"(cnt)); }
__device__ __forceinline__ void mbar_expect_tx(uint32_t bar, uint32_t bytes) { asm volatile("mbarrier.arrive.expect_tx.shared::cta.b64 _, [%0], %1;" :: "r"(bar), "r"(bytes) : "memory"); }
__device__ __forceinline__ void mbar_arrive_n(uint32_t bar, uint32_t n) { asm volatile("mbarrier.arrive.shared::cta.b64 _, [%0], %1;" :: "r"(bar), "r"(n) : "memory"); }
__device__ __forceinline__ void mbar_arrive(uint32_t bar) { asm volatile("mbarrier.arrive.shared::cta.b64 _, [%0];" :: "r"(bar) : "memory"); }
__device__ __forceinline__ bool mbar_try(uint32_t bar, uint32_t parity) {
  uint32_t ok;
  asm volatile("{\n.reg .pred p;\nmbarrier.try_wait.parity.shared::cta.b64 p, [%1], %2;\nselp.u32 %0, 1, 0, p;\n}" : "=r"(ok) : "r"(bar), "r"(parity) : "memory");
  return ok;
}
#define WAIT_TIMEOUT(n) if (++(n) > (1u << 22)) __trap();
__device__ __forceinline__ void mbar_wait(uint32_t bar, uint32_t parity) {
  if (mbar_try(bar, parity)) return;
  uint32_t n = 0;
  while (!mbar_try(bar, parity)) { WAIT_TIMEOUT(n) }
}
__device__ __forceinline__ void fence_proxy_async() { asm volatile("fence.proxy.async.shared::cta;" ::: "memory"); }
__device__ __forceinline__ void wgmma_fence() { asm volatile("wgmma.fence.sync.aligned;" ::: "memory"); }
__device__ __forceinline__ void wgmma_commit() { asm volatile("wgmma.commit_group.sync.aligned;" ::: "memory"); }
template<int N> __device__ __forceinline__ void wgmma_wait() { asm volatile("wgmma.wait_group.sync.aligned %0;" :: "n"(N) : "memory"); }
template<int N> __device__ __forceinline__ void fence_regs(float (&d)[N]) {
  #pragma unroll
  for (int i = 0; i < N; i++) asm volatile("" : "+f"(d[i]) :: "memory");
}
__device__ __forceinline__ void named_bar(int id, int n) { asm volatile("bar.sync %0, %1;" :: "r"(id), "r"(n) : "memory"); }
__device__ __forceinline__ bool named_bar_or(int id, int n, bool v) {
  uint32_t r;
  asm volatile("{\n.reg .pred p, q;\nsetp.ne.u32 q, %3, 0;\nbar.red.or.pred p, %1, %2, q;\nselp.u32 %0, 1, 0, p;\n}" : "=r"(r) : "r"(id), "r"(n), "r"((uint32_t)v) : "memory");
  return r;
}
__device__ __forceinline__ void tma2d(uint32_t dst, const CUtensorMap* tm, int c0, int c1, uint32_t bar) {
  asm volatile("cp.async.bulk.tensor.2d.shared::cluster.global.mbarrier::complete_tx::bytes [%0], [%1, {%3, %4}], [%2];"
    :: "r"(dst), "l"(tm), "r"(bar), "r"(c0), "r"(c1) : "memory");
}
__device__ __forceinline__ void tma3d(uint32_t dst, const CUtensorMap* tm, int c0, int c1, int c2, uint32_t bar) {
  asm volatile("cp.async.bulk.tensor.3d.shared::cluster.global.mbarrier::complete_tx::bytes [%0], [%1, {%3, %4, %5}], [%2];"
    :: "r"(dst), "l"(tm), "r"(bar), "r"(c0), "r"(c1), "r"(c2) : "memory");
}
__device__ __forceinline__ void tma3d_hint(uint32_t dst, const CUtensorMap* tm, int c0, int c1, int c2, uint32_t bar, uint64_t pol) {
  asm volatile("cp.async.bulk.tensor.3d.shared::cluster.global.mbarrier::complete_tx::bytes.L2::cache_hint [%0], [%1, {%3, %4, %5}], [%2], %6;"
    :: "r"(dst), "l"(tm), "r"(bar), "r"(c0), "r"(c1), "r"(c2), "l"(pol) : "memory");
}
__device__ __forceinline__ void bulk_g2s(uint32_t dst, const void* src, uint32_t bytes, uint32_t bar) {
  asm volatile("cp.async.bulk.shared::cluster.global.mbarrier::complete_tx::bytes [%0], [%1], %2, [%3];" :: "r"(dst), "l"(src), "r"(bytes), "r"(bar) : "memory");
}
__device__ __forceinline__ void bulk_s2g(void* dst, uint32_t src, uint32_t bytes) {
  asm volatile("cp.async.bulk.global.shared::cta.bulk_group [%0], [%1], %2;" :: "l"(dst), "r"(src), "r"(bytes) : "memory");
}
__device__ __forceinline__ void bulk_commit() { asm volatile("cp.async.bulk.commit_group;" ::: "memory"); }
__device__ __forceinline__ void bulk_wait_read() { asm volatile("cp.async.bulk.wait_group.read 0;" ::: "memory"); }
__device__ __forceinline__ void bulk_wait_all() { asm volatile("cp.async.bulk.wait_group 0;" ::: "memory"); }
__device__ __forceinline__ unsigned ld_acquire(const unsigned* p) { unsigned v; asm volatile("ld.acquire.gpu.global.u32 %0, [%1];" : "=r"(v) : "l"(p) : "memory"); return v; }
__device__ __forceinline__ void st_release(unsigned* p, unsigned v) { asm volatile("st.release.gpu.global.u32 [%0], %1;" :: "l"(p), "r"(v) : "memory"); }
__device__ __forceinline__ uint32_t poll_flags4(const unsigned* p, unsigned want) {
  uint32_t a, b, c, d;
  asm volatile("ld.volatile.global.v4.u32 {%0, %1, %2, %3}, [%4];" : "=r"(a), "=r"(b), "=r"(c), "=r"(d) : "l"(p) : "memory");
  return (a == want ? 1u : 0u) | (b == want ? 2u : 0u) | (c == want ? 4u : 0u) | (d == want ? 8u : 0u);
}
__device__ __forceinline__ void fence_proxy_async_global() { asm volatile("fence.proxy.async.global;" ::: "memory"); }
__device__ __forceinline__ uint32_t mapa(uint32_t addr, uint32_t cta) { uint32_t r; asm("mapa.shared::cluster.u32 %0, %1, %2;" : "=r"(r) : "r"(addr), "r"(cta)); return r; }
__device__ __forceinline__ void st_async_v4(uint32_t addr, float a, float b, float c, float d, uint32_t mbar) {
  asm volatile("st.async.weak.shared::cluster.mbarrier::complete_tx::bytes.v4.f32 [%0], {%1, %2, %3, %4}, [%5];" :: "r"(addr), "f"(a), "f"(b), "f"(c), "f"(d), "r"(mbar) : "memory");
}
__device__ __forceinline__ void mbar_wait_cluster(uint32_t bar, uint32_t parity) {
  uint32_t ok, n = 0;
  do {
    asm volatile("{\n.reg .pred p;\nmbarrier.try_wait.parity.acquire.cluster.shared::cta.b64 p, [%1], %2;\nselp.u32 %0, 1, 0, p;\n}" : "=r"(ok) : "r"(bar), "r"(parity) : "memory");
    if (!ok && ++n > (1u << 22)) __trap();
  } while (!ok);
}
__device__ __forceinline__ float ex2(float x) { float y; asm("ex2.approx.ftz.f32 %0, %1;" : "=f"(y) : "f"(x)); return y; }
__device__ __forceinline__ uint32_t pack_bf16(float lo, float hi) { uint32_t r; asm("cvt.rn.bf16x2.f32 %0, %1, %2;" : "=r"(r) : "f"(hi), "f"(lo)); return r; }
__device__ __forceinline__ void stsm_x2_t(uint32_t addr, uint32_t r0, uint32_t r1) {
  asm volatile("stmatrix.sync.aligned.m8n8.x2.trans.shared.b16 [%0], {%1, %2};" :: "r"(addr), "r"(r0), "r"(r1) : "memory");
}
__device__ __forceinline__ uint32_t bf16x2_chk(uint32_t u, uint32_t v, uint32_t c) { uint32_t r; asm("fma.rn.bf16x2 %0, %1, %2, %3;" : "=r"(r) : "r"(u), "r"(v), "r"(c)); return r; }
__device__ __forceinline__ void prefetch3d(const CUtensorMap* tm, int c0, int c1, int c2) {
  asm volatile("cp.async.bulk.prefetch.tensor.3d.L2.global.tile [%0, {%1, %2, %3}];" :: "l"(tm), "r"(c0), "r"(c1), "r"(c2) : "memory");
}
__device__ __forceinline__ void prefetch_tmap(const CUtensorMap* tm) { asm volatile("prefetch.tensormap [%0];" :: "l"(tm) : "memory"); }
__device__ __forceinline__ void prefetch2d(const CUtensorMap* tm, int c0, int c1) {
  asm volatile("cp.async.bulk.prefetch.tensor.2d.L2.global.tile [%0, {%1, %2}];" :: "l"(tm), "r"(c0), "r"(c1) : "memory");
}
__device__ __forceinline__ void stsm_x4_t(uint32_t addr, uint32_t r0, uint32_t r1, uint32_t r2, uint32_t r3) {
  asm volatile("stmatrix.sync.aligned.m8n8.x4.trans.shared.b16 [%0], {%1, %2, %3, %4};" :: "r"(addr), "r"(r0), "r"(r1), "r"(r2), "r"(r3) : "memory");
}
__device__ __forceinline__ uint64_t make_desc(uint32_t addr) {
  return (uint64_t)((addr & 0x3FFFF) >> 4) | ((uint64_t)1 << 16) | ((uint64_t)(1024 >> 4) << 32) | ((uint64_t)1 << 62);
}
template<int TA> __device__ __forceinline__ void wgmma144(float (&d)[72], uint64_t da, uint64_t db, int scale_d) {
  asm volatile("{\n.reg .pred p;\nsetp.ne.b32 p, %74, 0;\n"
    "wgmma.mma_async.sync.aligned.m64n144k16.f32.bf16.bf16 "
    "{%0, %1, %2, %3, %4, %5, %6, %7, %8, %9, %10, %11, "
    "%12, %13, %14, %15, %16, %17, %18, %19, %20, %21, %22, %23, "
    "%24, %25, %26, %27, %28, %29, %30, %31, %32, %33, %34, %35, "
    "%36, %37, %38, %39, %40, %41, %42, %43, %44, %45, %46, %47, "
    "%48, %49, %50, %51, %52, %53, %54, %55, %56, %57, %58, %59, "
    "%60, %61, %62, %63, %64, %65, %66, %67, %68, %69, %70, %71}, "
    "%72, %73, p, 1, 1, %75, 0;\n}\n"
    : "+f"(d[0]), "+f"(d[1]), "+f"(d[2]), "+f"(d[3]), "+f"(d[4]), "+f"(d[5]), "+f"(d[6]), "+f"(d[7]),
      "+f"(d[8]), "+f"(d[9]), "+f"(d[10]), "+f"(d[11]), "+f"(d[12]), "+f"(d[13]), "+f"(d[14]), "+f"(d[15]),
      "+f"(d[16]), "+f"(d[17]), "+f"(d[18]), "+f"(d[19]), "+f"(d[20]), "+f"(d[21]), "+f"(d[22]), "+f"(d[23]),
      "+f"(d[24]), "+f"(d[25]), "+f"(d[26]), "+f"(d[27]), "+f"(d[28]), "+f"(d[29]), "+f"(d[30]), "+f"(d[31]),
      "+f"(d[32]), "+f"(d[33]), "+f"(d[34]), "+f"(d[35]), "+f"(d[36]), "+f"(d[37]), "+f"(d[38]), "+f"(d[39]),
      "+f"(d[40]), "+f"(d[41]), "+f"(d[42]), "+f"(d[43]), "+f"(d[44]), "+f"(d[45]), "+f"(d[46]), "+f"(d[47]),
      "+f"(d[48]), "+f"(d[49]), "+f"(d[50]), "+f"(d[51]), "+f"(d[52]), "+f"(d[53]), "+f"(d[54]), "+f"(d[55]),
      "+f"(d[56]), "+f"(d[57]), "+f"(d[58]), "+f"(d[59]), "+f"(d[60]), "+f"(d[61]), "+f"(d[62]), "+f"(d[63]),
      "+f"(d[64]), "+f"(d[65]), "+f"(d[66]), "+f"(d[67]), "+f"(d[68]), "+f"(d[69]), "+f"(d[70]), "+f"(d[71])
    : "l"(da), "l"(db), "r"(scale_d), "n"(TA));
}
template<int TA> __device__ __forceinline__ void wgmma72(float (&d)[36], uint64_t da, uint64_t db, int scale_d) {
  asm volatile("{\n.reg .pred p;\nsetp.ne.b32 p, %38, 0;\n"
    "wgmma.mma_async.sync.aligned.m64n72k16.f32.bf16.bf16 "
    "{%0, %1, %2, %3, %4, %5, %6, %7, %8, %9, %10, %11, "
    "%12, %13, %14, %15, %16, %17, %18, %19, %20, %21, %22, %23, "
    "%24, %25, %26, %27, %28, %29, %30, %31, %32, %33, %34, %35}, "
    "%36, %37, p, 1, 1, %39, 0;\n}\n"
    : "+f"(d[0]), "+f"(d[1]), "+f"(d[2]), "+f"(d[3]), "+f"(d[4]), "+f"(d[5]), "+f"(d[6]), "+f"(d[7]),
      "+f"(d[8]), "+f"(d[9]), "+f"(d[10]), "+f"(d[11]), "+f"(d[12]), "+f"(d[13]), "+f"(d[14]), "+f"(d[15]),
      "+f"(d[16]), "+f"(d[17]), "+f"(d[18]), "+f"(d[19]), "+f"(d[20]), "+f"(d[21]), "+f"(d[22]), "+f"(d[23]),
      "+f"(d[24]), "+f"(d[25]), "+f"(d[26]), "+f"(d[27]), "+f"(d[28]), "+f"(d[29]), "+f"(d[30]), "+f"(d[31]),
      "+f"(d[32]), "+f"(d[33]), "+f"(d[34]), "+f"(d[35])
    : "l"(da), "l"(db), "r"(scale_d), "n"(TA));
}

__device__ __forceinline__ void slow_item(uint32_t os, uint32_t qs, const __nv_bfloat16* __restrict__ X, const __nv_bfloat16* __restrict__ W,
                                          const __nv_bfloat16* __restrict__ K, const __nv_bfloat16* __restrict__ V, int warp, int lane) {
  for (int q = warp; q < SQ; q += 4) {
    {
      float q0 = 0.f, q1 = 0.f, q2 = 0.f, q3 = 0.f;
      for (int k = 0; k < DM; k++) {
        const float xv = __bfloat162float(X[q * DM + k]);
        const uint2 ww = *reinterpret_cast<const uint2*>(W + (size_t)k * (NH * DH) + lane * 4);
        q0 = fmaf(xv, __uint_as_float(ww.x << 16), q0); q1 = fmaf(xv, __uint_as_float(ww.x & 0xffff0000u), q1);
        q2 = fmaf(xv, __uint_as_float(ww.y << 16), q2); q3 = fmaf(xv, __uint_as_float(ww.y & 0xffff0000u), q3);
      }
      const float c = 0.08838834764831845f * 1.4426950408889634f;
      const uint32_t u0 = pack_bf16(q0 * c, q1 * c), u1 = pack_bf16(q2 * c, q3 * c);
      __syncwarp();
      asm volatile("st.shared.v4.f32 [%0], {%1, %2, %3, %4};" :: "r"(qs + lane * 16), "f"(__uint_as_float(u0 << 16)), "f"(__uint_as_float(u0 & 0xffff0000u)),
                   "f"(__uint_as_float(u1 << 16)), "f"(__uint_as_float(u1 & 0xffff0000u)) : "memory");
      __syncwarp();
    }
    float s[16];
    #pragma unroll
    for (int t = 0; t < 16; t++) s[t] = 0.f;
    for (int ch = 0; ch < 16; ch++) {
      float qf[8];
      asm volatile("ld.shared.v4.f32 {%0, %1, %2, %3}, [%4];" : "=f"(qf[0]), "=f"(qf[1]), "=f"(qf[2]), "=f"(qf[3]) : "r"(qs + ch * 32));
      asm volatile("ld.shared.v4.f32 {%0, %1, %2, %3}, [%4];" : "=f"(qf[4]), "=f"(qf[5]), "=f"(qf[6]), "=f"(qf[7]) : "r"(qs + ch * 32 + 16));
      #pragma unroll
      for (int t = 0; t < 16; t++) {
        const uint4 kk = *reinterpret_cast<const uint4*>(K + (size_t)(t * 32 + lane) * DH + ch * 8);
        s[t] = fmaf(qf[0], __uint_as_float(kk.x << 16), s[t]); s[t] = fmaf(qf[1], __uint_as_float(kk.x & 0xffff0000u), s[t]);
        s[t] = fmaf(qf[2], __uint_as_float(kk.y << 16), s[t]); s[t] = fmaf(qf[3], __uint_as_float(kk.y & 0xffff0000u), s[t]);
        s[t] = fmaf(qf[4], __uint_as_float(kk.z << 16), s[t]); s[t] = fmaf(qf[5], __uint_as_float(kk.z & 0xffff0000u), s[t]);
        s[t] = fmaf(qf[6], __uint_as_float(kk.w << 16), s[t]); s[t] = fmaf(qf[7], __uint_as_float(kk.w & 0xffff0000u), s[t]);
      }
    }
    float m = s[0];
    #pragma unroll
    for (int t = 1; t < 16; t++) m = fmaxf(m, s[t]);
    #pragma unroll
    for (int o = 16; o > 0; o >>= 1) m = fmaxf(m, __shfl_xor_sync(0xffffffffu, m, o));
    float l = 0.f;
    #pragma unroll
    for (int t = 0; t < 16; t++) { s[t] = exp2f(s[t] - m); l += s[t]; }
    #pragma unroll
    for (int o = 16; o > 0; o >>= 1) l += __shfl_xor_sync(0xffffffffu, l, o);
    float o0 = 0.f, o1 = 0.f, o2 = 0.f, o3 = 0.f;
    #pragma unroll
    for (int t = 0; t < 16; t++) {
      for (int src = 0; src < 32; src++) {
        const float p = __shfl_sync(0xffffffffu, s[t], src);
        const uint2 vv = *reinterpret_cast<const uint2*>(V + (size_t)(t * 32 + src) * DH + lane * 4);
        o0 = fmaf(p, __uint_as_float(vv.x << 16), o0); o1 = fmaf(p, __uint_as_float(vv.x & 0xffff0000u), o1);
        o2 = fmaf(p, __uint_as_float(vv.y << 16), o2); o3 = fmaf(p, __uint_as_float(vv.y & 0xffff0000u), o3);
      }
    }
    const float inv = 1.f / l;
    const uint32_t oa = os + (lane >> 4) * BT + q * 128 + ((((lane & 15) >> 1) ^ (q & 7)) << 4) + (lane & 1) * 8;
    asm volatile("st.shared.v2.u32 [%0], {%1, %2};" :: "r"(oa), "r"(pack_bf16(o0 * inv, o1 * inv)), "r"(pack_bf16(o2 * inv, o3 * inv)) : "memory");
  }
}

template<int PART>
__device__ __forceinline__ void proj_part(float (&acc0)[72], float (&acc1)[72], uint32_t sb, uint32_t slot, int accumulate) {
  const uint64_t db = make_desc(sb + aux_off(slot)), da = make_desc(sb + aux_off(slot) + BT);
  if (PART == 0) wgmma_fence();
  wgmma144<1>(acc0, da + ((PART * 4096) >> 4), db + ((PART * 64) >> 4), PART ? 1 : accumulate);
  wgmma144<1>(acc1, da + ((8192 + PART * 4096) >> 4), db + ((PART * 64) >> 4), PART ? 1 : accumulate);
  wgmma144<1>(acc0, da + ((PART * 4096 + 2048) >> 4), db + ((PART * 64 + 32) >> 4), 1);
  wgmma144<1>(acc1, da + ((8192 + PART * 4096 + 2048) >> 4), db + ((PART * 64 + 32) >> 4), 1);
  wgmma_commit();
}
__device__ __forceinline__ void proj_wait(uint32_t fullbar, uint32_t& phbits, uint32_t slot) {
  mbar_wait(fullbar + 8u * slot, (phbits >> slot) & 1);
  phbits ^= 1u << slot;
}
__device__ __forceinline__ void proj_chunk(float (&acc0)[72], float (&acc1)[72], uint32_t sb, uint32_t fullbar, uint32_t& phbits, uint32_t slot, int accumulate) {
  proj_wait(fullbar, phbits, slot);
  proj_part<0>(acc0, acc1, sb, slot, accumulate);
  proj_part<1>(acc0, acc1, sb, slot, 1);
}

template<int PART> __device__ __forceinline__ void s_batch(float (&acc)[36], uint32_t ktile, uint32_t qhalf) {
  const uint64_t da = make_desc(ktile + PART * 8192), db = make_desc(qhalf + PART * BT);
  if (PART == 0) wgmma_fence();
  #pragma unroll
  for (int ks = 0; ks < 4; ks++) wgmma72<0>(acc, da + ((ks * 32) >> 4), db + ((ks * 32) >> 4), (PART | ks) != 0);
  wgmma_commit();
}
template<int PART> __device__ __forceinline__ void exp_part(float (&acc)[36], float* l, uint32_t pa) {
  #pragma unroll
  for (int ii = 2 * PART; ii < 2 * PART + 2; ii++) {
    float p[8];
    #pragma unroll
    for (int e = 0; e < 8; e++) p[e] = ex2(acc[8 * ii + e]);
    l[4 * ii + 0] += p[0] + p[2]; l[4 * ii + 1] += p[1] + p[3];
    l[4 * ii + 2] += p[4] + p[6]; l[4 * ii + 3] += p[5] + p[7];
    stsm_x4_t(pa + ii * 2048, pack_bf16(p[0], p[1]), pack_bf16(p[2], p[3]), pack_bf16(p[4], p[5]), pack_bf16(p[6], p[7]));
  }
  if (PART == 1) {
    float p[4];
    #pragma unroll
    for (int e = 0; e < 4; e++) p[e] = ex2(acc[32 + e]);
    l[16] += p[0] + p[2]; l[17] += p[1] + p[3];
    stsm_x2_t(pa + 4 * 2048, pack_bf16(p[0], p[1]), pack_bf16(p[2], p[3]));
  }
}

__device__ __forceinline__ void finish_out(float (&keep)[72], float (&send)[72], __nv_bfloat16* __restrict__ out, uint32_t sb, int g, int cb, int kh, int tid) {
  const int t = tid & 127, warp = (tid >> 5) & 3, lane = tid & 31;
  const uint32_t xbar = sb + OFF_BAR + 8u * B_X_FULL;
  {
    const uint32_t rdst = mapa(sb + OFF_KV + t * 16, 1 - kh), rbar = mapa(xbar, 1 - kh);
    #pragma unroll
    for (int i = 0; i < 18; i++) st_async_v4(rdst + i * 2048, send[4 * i], send[4 * i + 1], send[4 * i + 2], send[4 * i + 3], rbar);
  }
  mbar_wait_cluster(xbar, 0);
  const uint32_t st_off = (uint32_t)((8 * (lane >> 4) + (lane & 7)) * 128 + (((2 * warp + ((lane >> 3) & 1)) ^ (lane & 7)) << 4));
  const uint32_t stage = sb + OFF_AUX;
  #pragma unroll
  for (int ii = 0; ii < 9; ii++) {
    float4 u, v;
    asm volatile("ld.shared.v4.f32 {%0, %1, %2, %3}, [%4];" : "=f"(u.x), "=f"(u.y), "=f"(u.z), "=f"(u.w) : "r"(sb + OFF_KV + t * 16 + (2 * ii) * 2048));
    asm volatile("ld.shared.v4.f32 {%0, %1, %2, %3}, [%4];" : "=f"(v.x), "=f"(v.y), "=f"(v.z), "=f"(v.w) : "r"(sb + OFF_KV + t * 16 + (2 * ii + 1) * 2048));
    stsm_x4_t(stage + st_off + ii * 2048, pack_bf16(keep[8 * ii] + u.x, keep[8 * ii + 1] + u.y), pack_bf16(keep[8 * ii + 2] + u.z, keep[8 * ii + 3] + u.w),
              pack_bf16(keep[8 * ii + 4] + v.x, keep[8 * ii + 5] + v.y), pack_bf16(keep[8 * ii + 6] + v.z, keep[8 * ii + 7] + v.w));
  }
  named_bar(3, 128);
  {
    __nv_bfloat16* op = out + (size_t)((g & 7) * SQ) * (2 * DM) + (g >> 3) * 512 + cb * 128 + kh * 64;
    const int ch = t & 7;
    #pragma unroll
    for (int r = 0; r < 9; r++) {
      const int row = r * 16 + (t >> 3);
      uint4 v;
      asm volatile("ld.shared.v4.u32 {%0, %1, %2, %3}, [%4];" : "=r"(v.x), "=r"(v.y), "=r"(v.z), "=r"(v.w) : "r"(stage + row * 128 + ((ch ^ (row & 7)) << 4)));
      *reinterpret_cast<uint4*>(op + (size_t)row * (2 * DM) + ch * 8) = v;
    }
  }
}

__global__ void __cluster_dims__(2, 1, 1) __launch_bounds__(NTHREADS, 1)
fused_kernel(const __grid_constant__ Params prm, const __grid_constant__ RawPtrs raw) {
  extern __shared__ __align__(1024) unsigned char smem[];
  const uint32_t sb = smem_u32(smem);
  const int tid = threadIdx.x, wg = tid >> 7, warp = (tid >> 5) & 3, lane = tid & 31;
  int g, j;
  { const int c = blockIdx.x >> 1; int mem;
    if (c < 4) { g = 15; mem = c; }
    else if (c < 36) { g = (c - 4) & 7; mem = (c - 4) >> 3; }
    else { g = 8 + (c - 36) % 7; mem = (c - 36) / 7; }
    j = 2 * mem + (blockIdx.x & 1); }
  const int br = g >> 3, b = g & 7;
  const int cb = j >> 1, kh = j & 1;
  const uint32_t bar = sb + OFF_BAR;
  auto BAR = [&](int i) { return bar + 8u * i; };

  if (tid == 32) { prefetch_tmap(&prm.x[br]); prefetch_tmap(&prm.wq[br]); prefetch_tmap(&prm.k[br]); prefetch_tmap(&prm.v[br]); prefetch_tmap(&prm.wo[br]); }
  if (tid == 0) {
    if (sb & 1023) __trap();
    prefetch2d(&prm.x[br], j * 64, b * SQ);
    prefetch3d(&prm.wq[br], 0, b * 64, 2 * j);
    for (int i = 0; i < NKV; i++) { mbar_init(BAR(B_K_FULL + i), 1); mbar_init(BAR(B_V_FULL + i), 1); mbar_init(BAR(B_KV_EMPTY + i), 4); }
    for (int i = 0; i < 4; i++) { mbar_init(BAR(B_AUXQ_FULL + i), 1); mbar_init(BAR(B_AUXO_FULL + i), 1); mbar_init(BAR(B_AUX_EMPTY + i), 4); }
    for (int i = 0; i < NP; i++) { mbar_init(BAR(B_P_FULL + i), 4); mbar_init(BAR(B_P_EMPTY + i), 4); }
    mbar_init(BAR(B_Q_FULL), 4); mbar_init(BAR(B_QA_FULL), 4); mbar_init(BAR(B_O_FREE), 1); mbar_init(BAR(B_QLD), 4); mbar_init(BAR(B_L_FULL), 4); mbar_init(BAR(B_O_STAGED), 4);
    for (int i = 0; i < 4; i++) mbar_init(BAR(B_FREEQ + i), 4);
    for (int i = 0; i < 4; i++) *reinterpret_cast<volatile uint32_t*>(smem + OFF_BAD + 4 * i) = 0;
    mbar_init(BAR(B_EPOCH), 1);
    mbar_init(BAR(B_X_FULL), 1);
    asm volatile("fence.mbarrier_init.release.cluster;" ::: "memory");
    mbar_expect_tx(BAR(B_X_FULL), 18 * 128 * 16);
  }
  __syncthreads();
  asm volatile("barrier.cluster.arrive.relaxed.aligned;" ::: "memory");

  if (wg == 0) {
    asm volatile("setmaxnreg.dec.sync.aligned.u32 %0;" :: "n"(REG_PROD));
    if (warp == 0 && lane == 0) {
      uint64_t pol; asm volatile("createpolicy.fractional.L2::evict_first.b64 %0, 1.0;" : "=l"(pol));
      const CUtensorMap* tk = &prm.k[br];
      const CUtensorMap* tv = &prm.v[br];
      uint32_t slot = 0, ph = 1;
      uint32_t fb1 = 0, fb2 = 0, fp1 = 0, fp2 = 0, kph = 0, vph = 0;
      #pragma unroll 1
      for (int i = 0; i < 4; i++) {
        const int row0 = ((b * NH) + 8 * i + j) * SK;
        #pragma unroll 1
        for (int t = 0; t < 16; t++) {
          const bool isv = (t == 15) || (t >= 2 && !(t & 1));
          const int idx = (t == 15) ? 7 : (isv ? (t >> 1) - 1 : (t + 1) >> 1);
          if (t == NKV) {
            mbar_wait(BAR(B_QLD), i & 1);
            #pragma unroll 1
            for (int u = NKV; u < NKV + (i == 0 ? KVPF0 : KVPF); u++) prefetch3d((u & 1) ? tk : tv, 0, row0 + ((u & 1) ? (u + 1) >> 1 : (u >> 1) - 1) * 64, 0);
          }
          mbar_wait(BAR(B_KV_EMPTY + slot), ph);
          if (fb2) mbar_wait(fb2, fp2);
          const uint32_t fb = BAR((isv ? B_V_FULL : B_K_FULL) + slot);
          mbar_expect_tx(fb, AT);
          tma3d_hint(sb + OFF_KV + slot * AT, isv ? tv : tk, 0, row0 + idx * 64, 0, fb, pol);
          fb2 = fb1; fp2 = fp1; fb1 = fb;
          if (isv) { fp1 = (vph >> slot) & 1; vph ^= 1u << slot; } else { fp1 = (kph >> slot) & 1; kph ^= 1u << slot; }
          if (++slot == NKV) { slot = 0; ph ^= 1; }
        }
      }
    } else if (warp == 1 && lane == 0) {
      mbar_wait(BAR(B_EPOCH), 0);
      const unsigned epoch = *reinterpret_cast<volatile uint32_t*>(smem + OFF_EPOCH);
      uint32_t eph = 0;
      auto o_chunks = [&](int w) {
        const unsigned* fl = &g_flagO[g * 32 + 8 * w + 4 * (1 - kh)];
        uint32_t ready = 0;
        const int npre = (w == 3) ? 3 : 2;
        auto arm = [&](int c) {
          const uint32_t slot = (w == 3) ? wide_slot(c) : (c & 1);
          mbar_wait(BAR(B_AUX_EMPTY + slot), (eph >> slot) & 1);
          eph ^= 1u << slot;
          const uint32_t fb = BAR(B_AUXO_FULL + slot);
          mbar_expect_tx(fb, AUX_SLOT);
          tma3d(sb + aux_off(slot) + BT, &prm.wo[br], 0, (8 * w + 2 * (c >> 1) + (1 - kh)) * DH + (c & 1) * 64, 2 * cb, fb);
        };
        for (int c = 0; c < npre; c++) arm(c);
        for (int c = 0; c < 8; c++) {
          const int jj = 2 * (c >> 1) + (1 - kh);
          const uint32_t slot = (w == 3) ? wide_slot(c) : (c & 1);
          if (c >= npre) arm(c);
          if (!(c & 1)) {
            uint32_t n = 0;
            while (!((ready >> (c >> 1)) & 1)) { ready = poll_flags4(fl, epoch + 1); WAIT_TIMEOUT(n) }
            (void)ld_acquire(fl + (c >> 1));
            fence_proxy_async_global();
          }
          bulk_g2s(sb + aux_off(slot), g_O + (size_t)(((w * 16 + g) * 8 + jj) * 2 + (c & 1)) * BT, BT, BAR(B_AUXO_FULL + slot));
        }
      };
      #pragma unroll 1
      for (int w = 0; w < 4; w++) o_chunks(w);
    } else if (warp == 2 && lane == 0) {
      const unsigned epoch = *reinterpret_cast<volatile unsigned*>(&g_epoch);
      *reinterpret_cast<volatile uint32_t*>(smem + OFF_EPOCH) = epoch;
      mbar_arrive(BAR(B_EPOCH));
      if (atomicAdd(&g_done, 1) == NCTA - 1) { g_done = 0; __threadfence(); *reinterpret_cast<volatile unsigned*>(&g_epoch) = epoch + 1; }
      for (int i = 0; i < 4; i++) {
        mbar_wait(BAR(B_O_STAGED), i & 1);
        if (i < 3) mbar_wait(BAR(B_QLD), (i + 1) & 1);
        bulk_s2g(g_O + (size_t)((i * 16 + g) * 8 + j) * 2 * BT, sb + OFF_P, 2 * BT);
        bulk_commit();
        bulk_wait_read();
        if (i < 3) mbar_arrive(BAR(B_O_FREE)); else mbar_arrive_n(BAR(B_AUX_EMPTY + 3), 4);
        bulk_wait_all();
        fence_proxy_async_global();
        st_release(&g_flagO[g * 32 + 8 * i + 4 * kh + cb], epoch + 1);
      }
    } else if (warp == 3 && lane == 0) {
      uint32_t qph = 0xf;
      #pragma unroll 1
      for (int i = 0; i < 4; i++) {
        #pragma unroll 1
        for (int kc = 0; kc < 8; kc++) {
          const uint32_t slot = q_slot_i(i, kc);
          mbar_wait(BAR(B_FREEQ + slot), (qph >> slot) & 1);
          qph ^= 1u << slot;
          const uint32_t dst = sb + aux_off(slot), fb = BAR(B_AUXQ_FULL + slot);
          mbar_expect_tx(fb, AUX_SLOT);
          tma2d(dst, &prm.x[br], kc * 64, b * SQ, fb);
          tma3d(dst + BT, &prm.wq[br], 0, kc * 64, 2 * (8 * i + j), fb);
        }
        if (i < 3) prefetch3d(&prm.wq[br], 0, b * 64, 2 * (8 * (i + 1) + j));
        prefetch3d(&prm.wo[br], 0, (8 * i + 2 * (b >> 1) + (1 - kh)) * DH + (b & 1) * 64, 2 * cb);
      }
    }
  } else if (wg == 1) {
    asm volatile("setmaxnreg.inc.sync.aligned.u32 %0;" :: "n"(REG_S));
    const uint32_t st_off = (uint32_t)((8 * (lane >> 4) + (lane & 7)) * 128 + (((2 * warp + ((lane >> 3) & 1)) ^ (lane & 7)) << 4));
    float sa[36], sc[36];
    uint32_t kph = 0;
    for (int i = 0; i < 4; i++) {
      float l[36];
      #pragma unroll
      for (int c = 0; c < 36; c++) l[c] = 0.f;
      uint32_t slot = (16 * i) % NKV;
      mbar_wait(BAR(B_K_FULL + slot), (kph >> slot) & 1);
      kph ^= 1u << slot;
      mbar_wait(BAR(B_QA_FULL), i & 1);
      s_batch<0>(sa, sb + OFF_KV + slot * AT, sb + OFF_Q);
      s_batch<1>(sa, sb + OFF_KV + slot * AT, sb + OFF_Q);
      mbar_wait(BAR(B_Q_FULL), i & 1);
      s_batch<0>(sc, sb + OFF_KV + slot * AT, sb + OFF_Q + 9216);
      if (i > 0) mbar_wait(BAR(B_O_FREE), (i - 1) & 1);
      #pragma unroll 1
      for (int jt = 0; jt < 7; jt++) {
        const int m = 8 * i + jt;
        const uint32_t pa = sb + OFF_P + (m & 1) * BT + st_off;
        const uint32_t nslot = (16 * i + 2 * jt + 1) % NKV;
        const uint32_t kt = sb + OFF_KV + slot * AT, kn = sb + OFF_KV + nslot * AT;
        const bool p_ok = mbar_try(BAR(B_P_EMPTY + (m & 1)), ((m >> 1) & 1) ^ 1);
        wgmma_wait<1>();
        fence_regs(sa);
        s_batch<1>(sc, kt, sb + OFF_Q + 9216);
        if (!p_ok) mbar_wait(BAR(B_P_EMPTY + (m & 1)), ((m >> 1) & 1) ^ 1);
        exp_part<0>(sa, l, pa);
        wgmma_wait<0>();
        fence_regs(sc);
        if (lane == 0) mbar_arrive(BAR(B_KV_EMPTY + slot));
        const bool k_ok = mbar_try(BAR(B_K_FULL + nslot), (kph >> nslot) & 1);
        exp_part<1>(sa, l, pa);
        if (!k_ok) mbar_wait(BAR(B_K_FULL + nslot), (kph >> nslot) & 1);
        kph ^= 1u << nslot;
        s_batch<0>(sa, kn, sb + OFF_Q);
        exp_part<0>(sc, l + 18, pa + 9216);
        s_batch<1>(sa, kn, sb + OFF_Q);
        exp_part<1>(sc, l + 18, pa + 9216);
        fence_proxy_async();
        __syncwarp();
        if (lane == 0) mbar_arrive(BAR(B_P_FULL + (m & 1)));
        s_batch<0>(sc, kn, sb + OFF_Q + 9216);
        slot = nslot;
      }
      {
        const int m = 8 * i + 7;
        const uint32_t pa = sb + OFF_P + (m & 1) * BT + st_off;
        wgmma_wait<1>();
        fence_regs(sa);
        s_batch<1>(sc, sb + OFF_KV + slot * AT, sb + OFF_Q + 9216);
        mbar_wait(BAR(B_P_EMPTY + (m & 1)), ((m >> 1) & 1) ^ 1);
        exp_part<0>(sa, l, pa);
        exp_part<1>(sa, l, pa);
        wgmma_wait<0>();
        fence_regs(sc);
        if (lane == 0) { mbar_arrive(BAR(B_KV_EMPTY + slot)); mbar_arrive(BAR((i < 3 ? B_FREEQ : B_AUX_EMPTY) + 2)); }
        exp_part<0>(sc, l + 18, pa + 9216);
        exp_part<1>(sc, l + 18, pa + 9216);
        fence_proxy_async();
        __syncwarp();
        if (lane == 0) mbar_arrive(BAR(B_P_FULL + (m & 1)));
      }
      {
        const bool b4 = lane & 16, b3 = lane & 8, b2 = lane & 4;
        float m1[18], m2[9], m3[5];
        #pragma unroll
        for (int k = 0; k < 18; k++) m1[k] = (b4 ? l[18 + k] : l[k]) + __shfl_xor_sync(0xffffffffu, b4 ? l[k] : l[18 + k], 16);
        #pragma unroll
        for (int k = 0; k < 9; k++) m2[k] = (b3 ? m1[9 + k] : m1[k]) + __shfl_xor_sync(0xffffffffu, b3 ? m1[k] : m1[9 + k], 8);
        #pragma unroll
        for (int k = 0; k < 5; k++) {
          const float hi = (k < 4) ? m2[5 + (k < 4 ? k : 0)] : 0.f;
          m3[k] = (b2 ? hi : m2[k]) + __shfl_xor_sync(0xffffffffu, b2 ? m2[k] : hi, 4);
        }
        float* lred = reinterpret_cast<float*>(smem + OFF_LRED) + warp * SQ + 2 * (lane & 3);
        const int base = (b4 ? 18 : 0) + (b3 ? 9 : 0) + (b2 ? 5 : 0);
        #pragma unroll
        for (int k = 0; k < 5; k++) if (k < 4 || !b2) lred[8 * ((base + k) >> 1) + ((base + k) & 1)] = m3[k];
      }
      named_bar(1, 128);
      {
        const float* lred = reinterpret_cast<const float*>(smem + OFF_LRED);
        float* invl = reinterpret_cast<float*>(smem + OFF_INVL);
        const int t = tid & 127;
        #pragma unroll
        for (int r = 0; r < 2; r++) {
          const int q = t + 128 * r;
          if (q < SQ) {
            const float s = (lred[q] + lred[SQ + q]) + (lred[2 * SQ + q] + lred[3 * SQ + q]);
            invl[q] = __frcp_rn(s);
            if (!(s >= 9.5367431640625e-7f && s <= 1.152921504606847e18f)) *reinterpret_cast<volatile uint32_t*>(smem + OFF_BAD + 4 * i) = 1;
          }
        }
      }
      __syncwarp();
      if (lane == 0) mbar_arrive(BAR(B_L_FULL));
    }
  } else {
    asm volatile("setmaxnreg.inc.sync.aligned.u32 %0;" :: "n"(REG_O));
    float acc0[72], acc1[72];
    if (wg == 2) {
    const uint32_t st_off = (uint32_t)((8 * (lane >> 4) + (lane & 7)) * 128 + (((2 * warp + ((lane >> 3) & 1)) ^ (lane & 7)) << 4));
    uint32_t aph = 0, vph = 0;
    for (int i = 0; i < 4; i++) {
      proj_chunk(acc0, acc1, sb, BAR(B_AUXQ_FULL), aph, 2, 0);
      #pragma unroll 1
      for (int kc = 1; kc < 8; kc++) {
        const uint32_t qs = q_slot_i(i, kc);
        proj_wait(BAR(B_AUXQ_FULL), aph, qs);
        proj_part<0>(acc0, acc1, sb, qs, 1);
        wgmma_wait<1>();
        if (lane == 0 && kc != (i == 0 ? 5 : 7)) mbar_arrive(BAR(((kc == 6 && i > 0) ? B_AUX_EMPTY : B_FREEQ) + q_slot_i(i, kc - 1)));
        proj_part<1>(acc0, acc1, sb, qs, 1);
        if (kc == 7 && lane == 0) mbar_arrive(BAR(B_QLD));
      }
      wgmma_wait<0>();
      fence_regs(acc0); fence_regs(acc1);
      if (lane == 0 && i > 0) mbar_arrive(BAR(B_AUX_EMPTY + 0));
      named_bar(2, 128);
      {
        const float c = 0.08838834764831845f * 1.4426950408889634f;
        #pragma unroll
        for (int ii = 0; ii < 4; ii++) {
          stsm_x4_t(sb + OFF_Q + st_off + ii * 2048, pack_bf16(acc0[8 * ii] * c, acc0[8 * ii + 1] * c), pack_bf16(acc0[8 * ii + 2] * c, acc0[8 * ii + 3] * c),
                    pack_bf16(acc0[8 * ii + 4] * c, acc0[8 * ii + 5] * c), pack_bf16(acc0[8 * ii + 6] * c, acc0[8 * ii + 7] * c));
          stsm_x4_t(sb + OFF_Q + BT + st_off + ii * 2048, pack_bf16(acc1[8 * ii] * c, acc1[8 * ii + 1] * c), pack_bf16(acc1[8 * ii + 2] * c, acc1[8 * ii + 3] * c),
                    pack_bf16(acc1[8 * ii + 4] * c, acc1[8 * ii + 5] * c), pack_bf16(acc1[8 * ii + 6] * c, acc1[8 * ii + 7] * c));
        }
        stsm_x2_t(sb + OFF_Q + st_off + 4 * 2048, pack_bf16(acc0[32] * c, acc0[33] * c), pack_bf16(acc0[34] * c, acc0[35] * c));
        stsm_x2_t(sb + OFF_Q + BT + st_off + 4 * 2048, pack_bf16(acc1[32] * c, acc1[33] * c), pack_bf16(acc1[34] * c, acc1[35] * c));
        fence_proxy_async();
        __syncwarp();
        if (lane == 0) mbar_arrive(BAR(B_QA_FULL));
        #pragma unroll
        for (int ii = 0; ii < 4; ii++) {
          stsm_x4_t(sb + OFF_Q + 9216 + st_off + ii * 2048, pack_bf16(acc0[36 + 8 * ii] * c, acc0[36 + 8 * ii + 1] * c), pack_bf16(acc0[36 + 8 * ii + 2] * c, acc0[36 + 8 * ii + 3] * c),
                    pack_bf16(acc0[36 + 8 * ii + 4] * c, acc0[36 + 8 * ii + 5] * c), pack_bf16(acc0[36 + 8 * ii + 6] * c, acc0[36 + 8 * ii + 7] * c));
          stsm_x4_t(sb + OFF_Q + BT + 9216 + st_off + ii * 2048, pack_bf16(acc1[36 + 8 * ii] * c, acc1[36 + 8 * ii + 1] * c), pack_bf16(acc1[36 + 8 * ii + 2] * c, acc1[36 + 8 * ii + 3] * c),
                    pack_bf16(acc1[36 + 8 * ii + 4] * c, acc1[36 + 8 * ii + 5] * c), pack_bf16(acc1[36 + 8 * ii + 6] * c, acc1[36 + 8 * ii + 7] * c));
        }
        stsm_x2_t(sb + OFF_Q + 9216 + st_off + 4 * 2048, pack_bf16(acc0[68] * c, acc0[69] * c), pack_bf16(acc0[70] * c, acc0[71] * c));
        stsm_x2_t(sb + OFF_Q + BT + 9216 + st_off + 4 * 2048, pack_bf16(acc1[68] * c, acc1[69] * c), pack_bf16(acc1[70] * c, acc1[71] * c));
      }
      fence_proxy_async();
      __syncwarp();
      if (lane == 0) mbar_arrive(BAR(B_Q_FULL));
      #pragma unroll 1
      for (int jt = 0; jt < 8; jt++) {
        const int n = 16 * i + (jt == 7 ? 15 : 2 * jt + 2);
        const uint32_t slot = n % NKV;
        const int m = 8 * i + jt;
        mbar_wait(BAR(B_V_FULL + slot), (vph >> slot) & 1);
        vph ^= 1u << slot;
        mbar_wait(BAR(B_P_FULL + (m & 1)), (m >> 1) & 1);
        const uint64_t da = make_desc(sb + OFF_KV + slot * AT), db = make_desc(sb + OFF_P + (m & 1) * BT);
        wgmma_fence();
        #pragma unroll
        for (int ks = 0; ks < 4; ks++) {
          wgmma144<1>(acc0, da + ((ks * 2048) >> 4), db + ((ks * 32) >> 4), (jt | ks) != 0);
          wgmma144<1>(acc1, da + ((8192 + ks * 2048) >> 4), db + ((ks * 32) >> 4), (jt | ks) != 0);
        }
        wgmma_commit();
        wgmma_wait<0>();
        if (lane == 0) { mbar_arrive(BAR(B_P_EMPTY + (m & 1))); mbar_arrive(BAR(B_KV_EMPTY + slot)); }
      }
      fence_regs(acc0); fence_regs(acc1);
      named_bar(2, 128);
      mbar_wait(BAR(B_L_FULL), i & 1);
      const float* invl = reinterpret_cast<const float*>(smem + OFF_INVL) + 2 * (lane & 3);
      uint32_t chk = 0, chk2 = 0;
      float2 iv = *reinterpret_cast<const float2*>(invl), iw = *reinterpret_cast<const float2*>(invl + 8);
      #pragma unroll
      for (int ii = 0; ii < 9; ii++) {
        float2 nv = iv, nw = iw;
        if (ii < 8) { nv = *reinterpret_cast<const float2*>(invl + 16 * (ii + 1)); nw = *reinterpret_cast<const float2*>(invl + 16 * (ii + 1) + 8); }
        {
          const uint32_t r0 = pack_bf16(acc0[8 * ii] * iv.x, acc0[8 * ii + 1] * iv.y), r1 = pack_bf16(acc0[8 * ii + 2] * iv.x, acc0[8 * ii + 3] * iv.y);
          const uint32_t r2 = pack_bf16(acc0[8 * ii + 4] * iw.x, acc0[8 * ii + 5] * iw.y), r3 = pack_bf16(acc0[8 * ii + 6] * iw.x, acc0[8 * ii + 7] * iw.y);
          stsm_x4_t(sb + OFF_P + st_off + ii * 2048, r0, r1, r2, r3);
          chk = bf16x2_chk(r0, r1, chk); chk2 = bf16x2_chk(r2, r3, chk2);
        }
        {
          const uint32_t r0 = pack_bf16(acc1[8 * ii] * iv.x, acc1[8 * ii + 1] * iv.y), r1 = pack_bf16(acc1[8 * ii + 2] * iv.x, acc1[8 * ii + 3] * iv.y);
          const uint32_t r2 = pack_bf16(acc1[8 * ii + 4] * iw.x, acc1[8 * ii + 5] * iw.y), r3 = pack_bf16(acc1[8 * ii + 6] * iw.x, acc1[8 * ii + 7] * iw.y);
          stsm_x4_t(sb + OFF_P + BT + st_off + ii * 2048, r0, r1, r2, r3);
          chk = bf16x2_chk(r0, r1, chk); chk2 = bf16x2_chk(r2, r3, chk2);
        }
        iv = nv; iw = nw;
      }
      chk = bf16x2_chk(chk, chk2, chk);
      const bool bad = ((chk & 0x7f80u) == 0x7f80u) || ((chk & 0x7f800000u) == 0x7f800000u) || (*reinterpret_cast<volatile uint32_t*>(smem + OFF_BAD + 4 * i) != 0);
      if (named_bar_or(2, 128, bad)) {
        const size_t off = (size_t)((b * NH) + 8 * i + j) * SK * DH;
        slow_item(sb + OFF_P, sb + OFF_LRED + warp * 576, raw.x[br] + b * SQ * DM, raw.wq[br] + (8 * i + j) * DH, raw.k[br] + off, raw.v[br] + off, warp, lane);
      }
      fence_proxy_async();
      __syncwarp();
      if (lane == 0) mbar_arrive(BAR(B_O_STAGED));
    }
    } else {
    asm volatile("barrier.cluster.wait.acquire.aligned;" ::: "memory");
    uint32_t aph = 0;
    proj_chunk(acc0, acc1, sb, BAR(B_AUXO_FULL), aph, 0, 0);
    wgmma_wait<0>();
    if (lane == 0) mbar_arrive(BAR(B_AUX_EMPTY + 0));
    #pragma unroll 1
    for (int c = 1; c < 24; c++) {
      proj_chunk(acc0, acc1, sb, BAR(B_AUXO_FULL), aph, c & 1, 1);
      wgmma_wait<0>();
      if (lane == 0) mbar_arrive(BAR((((c & 7) >= 6 && c < 16) ? B_FREEQ : B_AUX_EMPTY) + (c & 1)));
    }
    proj_chunk(acc0, acc1, sb, BAR(B_AUXO_FULL), aph, wide_slot(0), 1);
    #pragma unroll 1
    for (int c = 1; c < 8; c++) {
      proj_wait(BAR(B_AUXO_FULL), aph, wide_slot(c));
      proj_part<0>(acc0, acc1, sb, wide_slot(c), 1);
      wgmma_wait<1>();
      if (lane == 0 && wide_release(c - 1)) mbar_arrive(BAR(B_AUX_EMPTY + wide_slot(c - 1)));
      proj_part<1>(acc0, acc1, sb, wide_slot(c), 1);
    }
    wgmma_wait<0>();
    fence_regs(acc0); fence_regs(acc1);
    named_bar(3, 128);
    if (kh == 0) finish_out(acc0, acc1, raw.out, sb, g, cb, 0, tid);
    else finish_out(acc1, acc0, raw.out, sb, g, cb, 1, tid);
    }
  }
}

typedef CUresult (*EncodeFn)(CUtensorMap*, CUtensorMapDataType, cuuint32_t, void*, const cuuint64_t*, const cuuint64_t*, const cuuint32_t*, const cuuint32_t*,
                             CUtensorMapInterleave, CUtensorMapSwizzle, CUtensorMapL2promotion, CUtensorMapFloatOOBfill);

bool encode(EncodeFn fn, CUtensorMap* m, void* p, int rank, const cuuint64_t* dims, const cuuint64_t* strides, const cuuint32_t* box,
            CUtensorMapL2promotion promo = CU_TENSOR_MAP_L2_PROMOTION_NONE) {
  const cuuint32_t es[3] = {1, 1, 1};
  return fn(m, CU_TENSOR_MAP_DATA_TYPE_BFLOAT16, rank, p, dims, strides, box, es, CU_TENSOR_MAP_INTERLEAVE_NONE, CU_TENSOR_MAP_SWIZZLE_128B,
            promo, CU_TENSOR_MAP_FLOAT_OOB_FILL_NONE) == CUDA_SUCCESS;
}

}

extern "C" void kernel_launch(void* const* d_in, const int* in_sizes, int n_in, void* d_out, int out_size) {
  (void)in_sizes; (void)n_in; (void)out_size;
  static Params prm;
  static void* cached[11] = {};
  static bool ok = false;
  bool same = ok && cached[10] == d_out;
  for (int i = 0; i < 10 && same; i++) same = cached[i] == d_in[i];
  if (!same) {
    void* fp = nullptr;
    cudaDriverEntryPointQueryResult qr;
    if (cudaGetDriverEntryPoint("cuTensorMapEncodeTiled", &fp, cudaEnableDefault, &qr) != cudaSuccess || !fp) return;
    EncodeFn fn = (EncodeFn)fp;
    bool good = true;
    for (int s = 0; s < 2; s++) {
      void* x = d_in[5 * s + 0]; void* k = d_in[5 * s + 1]; void* v = d_in[5 * s + 2]; void* wq = d_in[5 * s + 3]; void* wo = d_in[5 * s + 4];
      { cuuint64_t d[2] = {DM, NB * SQ}, st[1] = {DM * 2}; cuuint32_t bx[2] = {64, SQ}; good &= encode(fn, &prm.x[s], x, 2, d, st, bx); }
      { cuuint64_t d[3] = {64, DM, NH * DH / 64}, st[2] = {NH * DH * 2, 128}; cuuint32_t bx[3] = {64, 64, 2}; good &= encode(fn, &prm.wq[s], wq, 3, d, st, bx); }
      { cuuint64_t d[3] = {64, (cuuint64_t)NB * NH * SK, 2}, st[2] = {DH * 2, 128}; cuuint32_t bx[3] = {64, 64, 2};
        good &= encode(fn, &prm.k[s], k, 3, d, st, bx); good &= encode(fn, &prm.v[s], v, 3, d, st, bx); }
      { cuuint64_t d[3] = {64, NH * DH, DM / 64}, st[2] = {DM * 2, 128}; cuuint32_t bx[3] = {64, 64, 2}; good &= encode(fn, &prm.wo[s], wo, 3, d, st, bx); }
    }
    if (!good) return;
    cudaFuncSetAttribute(fused_kernel, cudaFuncAttributeMaxDynamicSharedMemorySize, SMEM_BYTES);
    for (int i = 0; i < 10; i++) cached[i] = d_in[i];
    cached[10] = d_out;
    ok = true;
  }
  RawPtrs raw;
  raw.out = (__nv_bfloat16*)d_out;
  for (int s = 0; s < 2; s++) {
    raw.x[s] = (const __nv_bfloat16*)d_in[5 * s + 0]; raw.k[s] = (const __nv_bfloat16*)d_in[5 * s + 1];
    raw.v[s] = (const __nv_bfloat16*)d_in[5 * s + 2]; raw.wq[s] = (const __nv_bfloat16*)d_in[5 * s + 3];
  }
  fused_kernel<<<NCTA, NTHREADS, SMEM_BYTES, cudaStreamPerThread>>>(prm, raw);
}
```
